```python
import torch

def _softmax(x, axis=-1):
    return torch.softmax(x, dim=axis)
def _gelu(x):
    return torch.nn.functional.gelu(x, approximate="tanh")
def _silu(x):
    return torch.nn.functional.silu(x)
def _sigmoid(x):
    return torch.sigmoid(x)
def _layernorm(x, axis=-1, eps=1e-5):
    m = x.mean(dim=axis, keepdim=True)
    v = x.var(dim=axis, keepdim=True, unbiased=False)
    return (x - m) / torch.sqrt(v + eps)
def _scatter_add(tgt, idx, src, axis=0):
    return tgt.clone().index_add_(axis, idx, src)
def _segment_sum(src, seg, n):
    out = torch.zeros((n,) + src.shape[1:], dtype=src.dtype)
    return out.index_add_(0, seg, src)
def _pad(x, pw):
    flat = tuple(v for pair in reversed(pw) for v in pair)
    return torch.nn.functional.pad(x, flat)

kernel_name = 'concat_heads__gqa_block_cached__gqa_block_cached__near_ridge'

def setup_inputs():

    _w = (lambda a: (lambda t: t.to(torch.bfloat16) if t.is_floating_point() else t)(torch.as_tensor(a)))
    def _A_setup():
        B, Sq, D = 8, 80, 448
        Hq, Hkv, Sk, Dh = 16, 8, 1024, 256
        assert Hq % Hkv == 0, (Hq, Hkv)
        return {
            "x": _w((lambda *s: torch.randn(*s, dtype=torch.bfloat16) * 0.8)(B, Sq, D)),
            "k_cache": _w((lambda *s: torch.randn(*s, dtype=torch.bfloat16) * 0.8)(B, Hkv, Sk, Dh)),
            "v_cache": _w((lambda *s: torch.randn(*s, dtype=torch.bfloat16) * 0.05)(B, Hkv, Sk, Dh)),
            "wq": _w((lambda *s: torch.randn(*s, dtype=torch.bfloat16) * 0.8)(D, Hq * Dh) * (D ** -0.5)),
            "wo": _w((lambda *s: torch.randn(*s, dtype=torch.bfloat16) * 0.05)(Hq * Dh, D) * ((Hq * Dh) ** -0.5)),
        }
    _A_in = _A_setup()

    def _B_setup():
        B, Sq, D = 8, 80, 448
        Hq, Hkv, Sk, Dh = 16, 8, 1024, 256
        assert Hq % Hkv == 0, (Hq, Hkv)
        return {
            "x": _w((lambda *s: torch.randn(*s, dtype=torch.bfloat16) * 0.8)(B, Sq, D)),
            "k_cache": _w((lambda *s: torch.randn(*s, dtype=torch.bfloat16) * 0.8)(B, Hkv, Sk, Dh)),
            "v_cache": _w((lambda *s: torch.randn(*s, dtype=torch.bfloat16) * 0.05)(B, Hkv, Sk, Dh)),
            "wq": _w((lambda *s: torch.randn(*s, dtype=torch.bfloat16) * 0.8)(D, Hq * Dh) * (D ** -0.5)),
            "wo": _w((lambda *s: torch.randn(*s, dtype=torch.bfloat16) * 0.05)(Hq * Dh, D) * ((Hq * Dh) ** -0.5)),
        }
    _B_in = _B_setup()

    return {
        "A_x": _A_in["x"],
        "A_k_cache": _A_in["k_cache"],
        "A_v_cache": _A_in["v_cache"],
        "A_wq": _A_in["wq"],
        "A_wo": _A_in["wo"],
        "B_x": _B_in["x"],
        "B_k_cache": _B_in["k_cache"],
        "B_v_cache": _B_in["v_cache"],
        "B_wq": _B_in["wq"],
        "B_wo": _B_in["wo"],
    }

def reference(A_x, A_k_cache, A_v_cache, A_wq, A_wo, B_x, B_k_cache, B_v_cache, B_wq, B_wo):
    def _A_ref(x, k_cache, v_cache, wq, wo):
        B, Sq, D = x.shape
        Hq, Dh = 16, 256
        Hkv = k_cache.shape[1]
        rep = Hq // Hkv
        q = (lambda x, *d: x.permute(*d))((x @ wq).reshape(B, Sq, Hq, Dh), 0, 2, 1, 3)
        k = (lambda x, n, axis: torch.repeat_interleave(x, n, dim=axis))(k_cache, rep, axis=1)
        v = (lambda x, n, axis: torch.repeat_interleave(x, n, dim=axis))(v_cache, rep, axis=1)
        scores = torch.einsum("bhqd,bhkd->bhqk", q, k) * (Dh ** -0.5)
        p = _softmax(scores, axis=-1)
        o = torch.einsum("bhqk,bhkd->bhqd", p, v)
        return (lambda x, *d: x.permute(*d))(o, 0, 2, 1, 3).reshape(B, Sq, Hq * Dh) @ wo

    def _B_ref(x, k_cache, v_cache, wq, wo):
        B, Sq, D = x.shape
        Hq, Dh = 16, 256
        Hkv = k_cache.shape[1]
        rep = Hq // Hkv
        q = (lambda x, *d: x.permute(*d))((x @ wq).reshape(B, Sq, Hq, Dh), 0, 2, 1, 3)
        k = (lambda x, n, axis: torch.repeat_interleave(x, n, dim=axis))(k_cache, rep, axis=1)
        v = (lambda x, n, axis: torch.repeat_interleave(x, n, dim=axis))(v_cache, rep, axis=1)
        scores = torch.einsum("bhqd,bhkd->bhqk", q, k) * (Dh ** -0.5)
        p = _softmax(scores, axis=-1)
        o = torch.einsum("bhqk,bhkd->bhqd", p, v)
        return (lambda x, *d: x.permute(*d))(o, 0, 2, 1, 3).reshape(B, Sq, Hq * Dh) @ wo

    a = _A_ref(A_x, A_k_cache, A_v_cache, A_wq, A_wo)
    b = _B_ref(B_x, B_k_cache, B_v_cache, B_wq, B_wo)
    return torch.concatenate([a, b], axis=-1)
```

```cpp
#include <cuda_runtime.h>
#include <cuda_bf16.h>
#include <cuda.h>
#include <stdint.h>

namespace {

constexpr int kB = 8, kSq = 80, kD = 448, kHkv = 8, kSk = 1024, kDh = 256;
constexpr int kThreads = 384;

constexpr uint32_t OFF_Q = 0;
constexpr uint32_t OFF_KV = 81920;
constexpr uint32_t OFF_P = OFF_KV + 3 * 32768;
constexpr uint32_t OFF_SPARE = OFF_P + 20480;
constexpr uint32_t OFF_XCH = OFF_SPARE + 28672 - 2560;
constexpr uint32_t OFF_MISC = OFF_SPARE + 28672;
constexpr uint32_t OFF_NM = OFF_MISC;
constexpr uint32_t OFF_CONST = OFF_MISC + 1280;
constexpr uint32_t OFF_BAR = OFF_MISC + 1296;
constexpr uint32_t OFF_JUNK = OFF_MISC + 2048;
constexpr uint32_t SMEM_BYTES = 232448;

constexpr uint32_t BAR_X = OFF_BAR;
constexpr uint32_t BAR_WQF = BAR_X + 7 * 8;
constexpr uint32_t BAR_WQE = BAR_WQF + 8 * 8;
constexpr uint32_t BAR_KVF = BAR_WQE + 8 * 8;
constexpr uint32_t BAR_KVE = BAR_KVF + 3 * 8;
constexpr uint32_t BAR_WOF = BAR_KVE + 3 * 8;
constexpr uint32_t BAR_WOE = BAR_WOF + 7 * 8;
constexpr uint32_t BAR_STG = BAR_WOE + 7 * 8;
constexpr uint32_t BAR_JUNK = BAR_STG + 2 * 8;

constexpr int NB_ALL = 1, NB_WG = 2, NB_RED = 4, NB_TOK = 6, NB_HELP = 8, NB_OUT = 9, NB_O = 11;

#define KV_T0 2000
#define KV_PACE 1340
#define KV_PF_MODE 2
#define KV_J1 2
#define KV_EXTRA1 500
#define KV_PHASE 1300
#define WO_PF_AT 99
#define PROMO CU_TENSOR_MAP_L2_PROMOTION_L2_128B
#define WQ_PF 0
#define TOK_LEAD 4
#define KV_PF_LIMIT 6

struct Params {
    CUtensorMap x[2], k[2], v[2], wq[2], wo[2], kl[2], vl[2], out;
    __nv_bfloat16* outp;
    const char *wop[2], *kp[2], *vp[2];
};

__device__ unsigned int g_zero_cnt[16];

__device__ __forceinline__ unsigned long long gtime() {
    unsigned long long t;
    asm volatile("mov.u64 %0, %globaltimer;" : "=l"(t));
    return t;
}
#define CK(it, e) do { } while (0)
#define TS(i) do { } while (0)

__device__ __forceinline__ void mbar_init(uint32_t bar, uint32_t cnt) {
    asm volatile("mbarrier.init.shared::cta.b64 [%0], %1;" ::"r"(bar), "r"(cnt) : "memory");
}
__device__ __forceinline__ void mbar_expect_tx(uint32_t bar, uint32_t bytes) {
    asm volatile("mbarrier.arrive.expect_tx.shared::cta.b64 _, [%0], %1;" ::"r"(bar), "r"(bytes) : "memory");
}
__device__ __forceinline__ void mbar_arrive(uint32_t bar) {
    asm volatile("mbarrier.arrive.shared::cta.b64 _, [%0];" ::"r"(bar) : "memory");
}
__device__ __forceinline__ void mbar_wait(uint32_t bar, uint32_t parity) {
    asm volatile(
        "{\n"
        ".reg .pred p;\n"
        ".reg .u32 n;\n"
        "mov.u32 n, 0;\n"
        "LAB_WAIT:\n"
        "mbarrier.try_wait.parity.shared::cta.b64 p, [%0], %1;\n"
        "@p bra LAB_DONE;\n"
        "add.u32 n, n, 1;\n"
        "setp.lt.u32 p, n, 4000000;\n"
        "@p bra LAB_WAIT;\n"
        "trap;\n"
        "LAB_DONE:\n"
        "}\n" ::"r"(bar), "r"(parity) : "memory");
}
__device__ __forceinline__ void tma_load_3d(uint32_t dst, const CUtensorMap* map, uint32_t bar, int c0, int c1, int c2) {
    asm volatile(
        "cp.async.bulk.tensor.3d.shared::cluster.global.mbarrier::complete_tx::bytes [%0], [%1, {%3, %4, %5}], [%2];"
        ::"r"(dst), "l"(map), "r"(bar), "r"(c0), "r"(c1), "r"(c2) : "memory");
}
__device__ __forceinline__ void tma_load_3d_hint(uint32_t dst, const CUtensorMap* map, uint32_t bar, int c0, int c1, int c2,
                                                 uint64_t pol) {
    asm volatile(
        "cp.async.bulk.tensor.3d.shared::cluster.global.mbarrier::complete_tx::bytes.L2::cache_hint"
        " [%0], [%1, {%3, %4, %5}], [%2], %6;"
        ::"r"(dst), "l"(map), "r"(bar), "r"(c0), "r"(c1), "r"(c2), "l"(pol) : "memory");
}
__device__ __forceinline__ void tma_load_3d_mc(uint32_t dst, const CUtensorMap* map, uint32_t bar, int c0, int c1, int c2) {
    asm volatile(
        "cp.async.bulk.tensor.3d.shared::cluster.global.mbarrier::complete_tx::bytes.multicast::cluster"
        " [%0], [%1, {%3, %4, %5}], [%2], %6;"
        ::"r"(dst), "l"(map), "r"(bar), "r"(c0), "r"(c1), "r"(c2), "h"((uint16_t)3) : "memory");
}
__device__ __forceinline__ void mbar_arrive_both(uint32_t sb, uint32_t sbp, uint32_t off) {
    mbar_arrive(sb + off);
    asm volatile("mbarrier.arrive.shared::cluster.b64 _, [%0];" ::"r"(sbp + off) : "memory");
}
__device__ __forceinline__ bool mbar_test(uint32_t bar, uint32_t parity) {
    uint32_t r;
    asm volatile("{\n.reg .pred p;\nmbarrier.test_wait.parity.shared::cta.b64 p, [%1], %2;\nselp.u32 %0, 1, 0, p;\n}\n"
                 : "=r"(r) : "r"(bar), "r"(parity) : "memory");
    return r != 0;
}
__device__ __forceinline__ int lane_id() {
    int l;
    asm volatile("mov.u32 %0, %laneid;" : "=r"(l));
    return l;
}
__device__ __forceinline__ uint32_t wo_pos_off(int p) {
    return p == 0 ? OFF_SPARE : OFF_KV + (uint32_t)(p <= 2 ? p + 3 : p - 3) * 16384;
}
__device__ __forceinline__ void bar_arrive(int id, int n) { asm volatile("bar.arrive %0, %1;" ::"r"(id), "r"(n) : "memory"); }
__device__ __forceinline__ float rcp_approx(float x) {
    float y;
    asm("rcp.approx.ftz.f32 %0, %1;" : "=f"(y) : "f"(x));
    return y;
}
__device__ __forceinline__ void tma_touch_lines(uint32_t junk, const CUtensorMap* map, uint32_t bar, int line) {
    asm volatile(
        "cp.async.bulk.tensor.2d.shared::cluster.global.mbarrier::complete_tx::bytes [%0], [%1, {%3, %4}], [%2];"
        ::"r"(junk), "l"(map), "r"(bar), "r"(0), "r"(line) : "memory");
}
__device__ __forceinline__ uint32_t wq_pos_off(int p) {
    return (p < 3 ? OFF_Q + 32768 : OFF_KV + 65536 - 3 * 16384) + (uint32_t)p * 16384;
}
__device__ __forceinline__ void prefetch_tmap(const CUtensorMap* map) {
    asm volatile("prefetch.tensormap [%0];" ::"l"(map) : "memory");
}
__device__ __forceinline__ void wg_fence() { asm volatile("wgmma.fence.sync.aligned;" ::: "memory"); }
__device__ __forceinline__ void wg_commit() { asm volatile("wgmma.commit_group.sync.aligned;" ::: "memory"); }
template <int N>
__device__ __forceinline__ void wg_wait() { asm volatile("wgmma.wait_group.sync.aligned %0;" ::"n"(N) : "memory"); }
__device__ __forceinline__ void fence_async_smem() { asm volatile("fence.proxy.async.shared::cta;" ::: "memory"); }
__device__ __forceinline__ void fence_async_all() { asm volatile("fence.proxy.async;" ::: "memory"); }
__device__ __forceinline__ void bar_sync(int id, int n) { asm volatile("bar.sync %0, %1;" ::"r"(id), "r"(n) : "memory"); }
__device__ __forceinline__ bool bar_red_or(int id, int n, bool pred) {
    uint32_t r;
    asm volatile(
        "{\n.reg .pred p, q;\nsetp.ne.u32 p, %3, 0;\nbar.red.or.pred q, %1, %2, p;\nselp.u32 %0, 1, 0, q;\n}\n"
        : "=r"(r) : "r"(id), "r"(n), "r"((uint32_t)pred) : "memory");
    return r != 0;
}
__device__ __forceinline__ void reg_fence(float (&d)[40]) {
#pragma unroll
    for (int i = 0; i < 40; i++) asm volatile("" : "+f"(d[i])::"memory");
}

__device__ __forceinline__ uint32_t make_desc(uint32_t addr) { return ((addr & 0x3FFFF) >> 4) | (1u << 16); }

template <int TRANS_A>
__device__ __forceinline__ void wgmma_n80(float (&d)[40], uint32_t da, uint32_t db, uint32_t scale_d) {
    asm volatile(
        "{\n.reg .pred p;\n.reg .b64 da, db;\nsetp.ne.b32 p, %42, 0;\n"
        "mov.b64 da, {%40, %44};\nmov.b64 db, {%41, %44};\n"
        "wgmma.mma_async.sync.aligned.m64n80k16.f32.bf16.bf16 "
        "{%0, %1, %2, %3, %4, %5, %6, %7, %8, %9, %10, %11, %12, %13, %14, %15, %16, %17, %18, %19, "
        "%20, %21, %22, %23, %24, %25, %26, %27, %28, %29, %30, %31, %32, %33, %34, %35, %36, %37, %38, %39}, "
        "da, db, p, 1, 1, %43, 0;\n}\n"
        : "+f"(d[0]), "+f"(d[1]), "+f"(d[2]), "+f"(d[3]), "+f"(d[4]), "+f"(d[5]), "+f"(d[6]), "+f"(d[7]),
          "+f"(d[8]), "+f"(d[9]), "+f"(d[10]), "+f"(d[11]), "+f"(d[12]), "+f"(d[13]), "+f"(d[14]), "+f"(d[15]),
          "+f"(d[16]), "+f"(d[17]), "+f"(d[18]), "+f"(d[19]), "+f"(d[20]), "+f"(d[21]), "+f"(d[22]), "+f"(d[23]),
          "+f"(d[24]), "+f"(d[25]), "+f"(d[26]), "+f"(d[27]), "+f"(d[28]), "+f"(d[29]), "+f"(d[30]), "+f"(d[31]),
          "+f"(d[32]), "+f"(d[33]), "+f"(d[34]), "+f"(d[35]), "+f"(d[36]), "+f"(d[37]), "+f"(d[38]), "+f"(d[39])
        : "r"(da), "r"(db), "r"(scale_d), "n"(TRANS_A), "n"(0x40000040));
}

__device__ __forceinline__ uint32_t pack_bf16(float lo, float hi) {
    uint32_t r;
    asm("cvt.rn.bf16x2.f32 %0, %1, %2;" : "=r"(r) : "f"(hi), "f"(lo));
    return r;
}
__device__ __forceinline__ void stsm_x4_trans(uint32_t addr, uint32_t a, uint32_t b, uint32_t c, uint32_t d) {
    asm volatile("stmatrix.sync.aligned.m8n8.x4.trans.shared.b16 [%0], {%1, %2, %3, %4};"
                 ::"r"(addr), "r"(a), "r"(b), "r"(c), "r"(d) : "memory");
}
__device__ __forceinline__ float ex2(float x) {
    float y;
    asm("ex2.approx.ftz.f32 %0, %1;" : "=f"(y) : "f"(x));
    return y;
}
__device__ __forceinline__ float4 lds128(uint32_t addr) {
    float4 v;
    asm volatile("ld.shared.v4.f32 {%0, %1, %2, %3}, [%4];" : "=f"(v.x), "=f"(v.y), "=f"(v.z), "=f"(v.w) : "r"(addr) : "memory");
    return v;
}
__device__ __forceinline__ void sts128(uint32_t addr, float4 v) {
    asm volatile("st.shared.v4.f32 [%0], {%1, %2, %3, %4};" ::"r"(addr), "f"(v.x), "f"(v.y), "f"(v.z), "f"(v.w) : "memory");
}
__device__ __forceinline__ void sts64(uint32_t addr, float a, float b) {
    asm volatile("st.shared.v2.f32 [%0], {%1, %2};" ::"r"(addr), "f"(a), "f"(b) : "memory");
}

__device__ __forceinline__ void store_tile_T(uint32_t taddr, const float (&d)[40]) {
#pragma unroll
    for (int g = 0; g < 5; g++) {
        stsm_x4_trans(taddr + g * 2048, pack_bf16(d[8 * g + 0], d[8 * g + 1]), pack_bf16(d[8 * g + 2], d[8 * g + 3]),
                      pack_bf16(d[8 * g + 4], d[8 * g + 5]), pack_bf16(d[8 * g + 6], d[8 * g + 7]));
    }
}

__device__ __forceinline__ void store_tile_T_scaled(uint32_t taddr, const float (&d)[40], float c) {
#pragma unroll
    for (int g = 0; g < 5; g++) {
        stsm_x4_trans(taddr + g * 2048, pack_bf16(d[8 * g + 0] * c, d[8 * g + 1] * c), pack_bf16(d[8 * g + 2] * c, d[8 * g + 3] * c),
                      pack_bf16(d[8 * g + 4] * c, d[8 * g + 5] * c), pack_bf16(d[8 * g + 6] * c, d[8 * g + 7] * c));
    }
}
__device__ __forceinline__ void load_nm(float (&s)[40], uint32_t addr) {
#pragma unroll
    for (int g = 0; g < 10; g++) {
        const float4 v = lds128(addr + g * 16);
        s[4 * g + 0] = v.x; s[4 * g + 1] = v.y; s[4 * g + 2] = v.z; s[4 * g + 3] = v.w;
    }
}

__global__ void __cluster_dims__(2, 1, 1) __launch_bounds__(kThreads, 1)
fused_gqa_kernel(const __grid_constant__ Params prm) {
    extern __shared__ __align__(1024) unsigned char smem_raw[];
    const uint32_t sb = (uint32_t)__cvta_generic_to_shared(smem_raw);
    const int tid = threadIdx.x;
    const int warp = __shfl_sync(0xffffffffu, tid >> 5, 0), lane = tid & 31;
    const int bidx = blockIdx.x;
    const int br = bidx >> 6;
    const int kvh = (bidx >> 3) & 7;
    const int b = bidx & 7;
    const int rank = bidx & 1;

    if (warp == 8 && lane == 0) {
        TS(0);
        prefetch_tmap(&prm.x[br]);
        prefetch_tmap(&prm.wq[br]);
        if (sb & 1023) __trap();
        for (int i = 0; i < 7; i++) mbar_init(sb + BAR_X + 8 * i, 1);
        for (int i = 0; i < 8; i++) { mbar_init(sb + BAR_WQF + 8 * i, 1); mbar_init(sb + BAR_WQE + 8 * i, 16); }
        for (int i = 0; i < 3; i++) { mbar_init(sb + BAR_KVF + 8 * i, 1); mbar_init(sb + BAR_KVE + 8 * i, 8); }
        for (int i = 0; i < 7; i++) { mbar_init(sb + BAR_WOF + 8 * i, 1); mbar_init(sb + BAR_WOE + 8 * i, 16); }
        mbar_init(sb + BAR_STG, 1);
        mbar_init(sb + BAR_STG + 8, 1);
        mbar_init(sb + BAR_JUNK, 1);
        asm volatile("mbarrier.arrive.shared::cta.b64 _, [%0], 8;" ::"r"(sb + BAR_KVE) : "memory");
        asm volatile("mbarrier.arrive.shared::cta.b64 _, [%0], 8;" ::"r"(sb + BAR_KVE + 8) : "memory");
        asm volatile("fence.mbarrier_init.release.cluster;" ::: "memory");
    }
    if (tid < 256) {
        asm volatile("st.shared.f32 [%0], %1;" ::"r"(sb + OFF_NM + tid * 4), "f"(0.0f) : "memory");
        if (tid < 64) asm volatile("st.shared.f32 [%0], %1;" ::"r"(sb + OFF_NM + 1024 + tid * 4), "f"(0.0f) : "memory");
        if (tid == 64) asm volatile("st.shared.v2.u32 [%0], {%1, %2};" ::"r"(sb + OFF_CONST), "r"(16u), "r"(0xffff0000u) : "memory");
    }
    if (warp == 9 && lane == 0) {
        prefetch_tmap(&prm.k[br]); prefetch_tmap(&prm.v[br]); prefetch_tmap(&prm.kl[br]); prefetch_tmap(&prm.vl[br]);
    }
    __syncwarp();
    asm volatile("barrier.cluster.arrive.relaxed.aligned;" ::: "memory");
    if (warp == 8 && lane == 0) {
        mbar_expect_tx(sb + BAR_X, 10240);
        tma_load_3d(sb + OFF_Q, &prm.x[br], sb + BAR_X, 0, b * kSq, 0);
    }
    __syncwarp();
    asm volatile("barrier.cluster.wait.acquire.aligned;" ::: "memory");

    if (warp >= 8) {
        asm volatile("setmaxnreg.dec.sync.aligned.u32 24;");
        if (warp == 8) {
            if (lane == 0) {
                const CUtensorMap* mw = &prm.wq[br];
                int pos = 7, ph = 0;
                for (int s = 0; s < 28; s++) {
                    if (WQ_PF && s == 8) {
                        for (int i = 16 + b; i < 56; i += 8)
                            asm volatile("cp.async.bulk.prefetch.tensor.3d.L2.global.tile [%0, {%1, %2, %3}];"
                                         ::"l"(mw), "r"(0), "r"((i >> 1) * 16), "r"(kvh * 8 + (i & 1) * 4) : "memory");
                        if (kvh >= 3 && kvh < 7)
                            asm volatile("cp.async.bulk.prefetch.tensor.3d.L2.global.tile [%0, {%1, %2, %3}];"
                                         ::"l"(&prm.x[br]), "r"(0), "r"(b * kSq), "r"(kvh) : "memory");
                    }
                    if (s >= 8) mbar_wait(sb + BAR_WQE + 8 * pos, ((s >> 3) - 1) & 1);
                    TS(16 + s);
                    mbar_expect_tx(sb + BAR_WQF + 8 * pos, 16384);
                    tma_load_3d_mc(sb + wq_pos_off(pos) + rank * 8192, mw, sb + BAR_WQF + 8 * pos, 0, s * 16,
                                   kvh * 8 + rank * 4);
                    if ((s & 3) == 3 && s < 24) {
                        const int c = (s + 1) >> 2;
                        mbar_expect_tx(sb + BAR_X + 8 * c, 10240);
                        tma_load_3d(sb + OFF_Q + (c % 3) * 10240, &prm.x[br], sb + BAR_X + 8 * c, 0, b * kSq, c);
                    }
                    pos = (pos + 1) & 7;
                }
                const CUtensorMap* mo = &prm.wo[br];
                prefetch_tmap(mo);
                pos = 0;
                for (int st = 0; st < 28; st++) {
                    mbar_wait(sb + BAR_WOE + 8 * pos, ph);
                    TS(96 + st);
                    const int u = st - 4 * rank;
                    int row, col;
                    if (u >= 0 && u < 24) { row = (u & 7) * 64; col = (u >> 3) * 2 + rank; }
                    else { row = rank * 256 + (st & 3) * 64; col = 6; }
                    mbar_expect_tx(sb + BAR_WOF + 8 * pos, 16384);
                    tma_load_3d_mc(sb + wo_pos_off(pos) + rank * 8192, mo, sb + BAR_WOF + 8 * pos, 0, kvh * 512 + row, col);
                    if (++pos == 7) { pos = 0; ph ^= 1; }
                }
            }
        } else if (warp == 9) {
            if (lane == 0) {
                uint64_t pol;
                asm volatile("createpolicy.fractional.L2::evict_first.b64 %0, 1.0;" : "=l"(pol));
                const int row0 = (b * kHkv + kvh) * kSk;
                const uint32_t t0 = (uint32_t)gtime() + ((((uint32_t)bidx >> 1) * 27u) & 63u) * KV_PHASE / 64u;
                int slot = 0, use = 0, c = 0, pf = 0;
                uint32_t spins = 0;
                while (c < 32) {
                    const int now = (int)((uint32_t)gtime() - t0);
                    const bool due = now >= KV_T0 + pf * KV_PACE + min(pf, KV_J1) * KV_EXTRA1;
                    if ((c < pf || due) && mbar_test(sb + BAR_KVE + 8 * slot, use & 1)) {
                        TS(64 + c);
                        const uint32_t bar = sb + BAR_KVF + 8 * slot;
                        mbar_expect_tx(bar, 32768);
                        tma_load_3d_hint(sb + OFF_KV + slot * 32768, (c & 1) ? &prm.v[br] : &prm.k[br], bar, 0,
                                         row0 + (c >> 1) * 64, 0, pol);
                        if (++slot == 3) { slot = 0; use++; }
                        if (++c > pf) pf = c;
                    } else if (due && pf < KV_PF_LIMIT) {
                        asm volatile("mbarrier.expect_tx.shared::cta.b64 [%0], %1;" ::"r"(sb + BAR_JUNK), "r"(4096 / KV_PF_MODE) : "memory");
                        for (int i = 0; i < 4 / KV_PF_MODE; i++)
                            tma_touch_lines(sb + OFF_JUNK, (pf & 1) ? &prm.vl[br] : &prm.kl[br], sb + BAR_JUNK,
                                            (row0 + (pf >> 1) * 64) * (4 / KV_PF_MODE) + i * 64);
                        pf++;
                    } else {
                        __nanosleep(20);
                        if (++spins > 200000000u) __trap();
                    }
                }
                if (WO_PF_AT >= 29 && WO_PF_AT < 32) {
                    mbar_wait(sb + BAR_KVF + 8 * (WO_PF_AT % 3), (WO_PF_AT / 3) & 1);
                    for (int i = 10 + b; i < 56; i += 8) {
                        const int st = i >> 1, r = i & 1, u = st - 4 * r;
                        int row, col;
                        if (u >= 0 && u < 24) { row = (u & 7) * 64; col = (u >> 3) * 2 + r; }
                        else { row = r * 256 + (st & 3) * 64; col = 6; }
                        asm volatile("cp.async.bulk.prefetch.tensor.3d.L2.global.tile [%0, {%1, %2, %3}];"
                                     ::"l"(&prm.wo[br]), "r"(0), "r"(kvh * 512 + row), "r"(col) : "memory");
                    }
                }
                mbar_arrive(sb + BAR_JUNK);
                mbar_wait(sb + BAR_JUNK, 0);
            }
        } else {
            const int t = tid - 320;
            __nv_bfloat16* o = prm.outp + (size_t)(b * kSq + kvh * 10) * (2 * kD) + br * kD;
            for (int i = t; i < 560; i += 64) {
                const int r = i / 56, c = i % 56;
                *reinterpret_cast<uint4*>(o + (size_t)r * (2 * kD) + c * 8) = make_uint4(0, 0, 0, 0);
            }
            fence_async_all();
            __threadfence();
            bar_sync(NB_HELP, 64);
            if (t == 0) {
                prefetch_tmap(&prm.out);
                unsigned int* cnt = &g_zero_cnt[br * 8 + b];
                unsigned int old;
                asm volatile("atom.add.release.gpu.global.u32 %0, [%1], 1;" : "=r"(old) : "l"(cnt) : "memory");
                const unsigned int target = (old & ~7u) + 8u;
                unsigned int cur, n = 0;
#pragma unroll 1
                do {
                    asm volatile("ld.acquire.gpu.global.u32 %0, [%1];" : "=r"(cur) : "l"(cnt) : "memory");
                    if ((int)(cur - target) >= 0) break;
                    __nanosleep(500);
                } while (++n < 4000000u);
                if ((int)(cur - target) < 0) __trap();
            }
            bar_sync(NB_HELP, 64);
            fence_async_all();
            const int h = warp - 10;
            for (int t2 = 0; t2 < 4; t2++) {
                bar_sync(NB_OUT + h, 160);
                if (lane == 0) {
                    const int tile = h ? (t2 == 0 ? 6 : 2 * t2 - 1) : 2 * t2;
                    asm volatile("cp.reduce.async.bulk.tensor.2d.global.shared::cta.add.tile.bulk_group [%0, {%2, %3}], [%1];"
                                 ::"l"(&prm.out), "r"(sb + OFF_P + h * 10240), "r"(br * kD + tile * 64), "r"(b * kSq) : "memory");
                    asm volatile("cp.async.bulk.commit_group;" ::: "memory");
                    if (t2 == 3 && h == 0) TS(4);
                    asm volatile("cp.async.bulk.wait_group.read 0;" ::: "memory");
                    if (t2 == 3 && h == 0) TS(5);
                    mbar_arrive(sb + BAR_STG + 8 * h);
                }
                __syncwarp();
            }
        }
    } else {
        asm volatile("setmaxnreg.inc.sync.aligned.u32 240;");
        const int h = warp >> 2;
        const int w = warp & 3;
        const uint32_t st_off = (uint32_t)(((lane >> 4) * 8 + (lane & 7)) * 128 + (((2 * w + ((lane >> 3) & 1)) ^ (lane & 7)) << 4));

        float o[4][40];

        const bool lane0 = (lane == 0);
        uint32_t sbp;
        asm volatile("mapa.shared::cluster.u32 %0, %1, %2;" : "=r"(sbp) : "r"(sb), "r"(rank ^ 1));
        sbp = __shfl_sync(0xffffffffu, sbp, 0);

        {
            int pos = 7, xs = 0;
            for (int s = 0; s < 28; s++) {
                if ((s & 3) == 0) mbar_wait(sb + BAR_X + 8 * (s >> 2), 0);
                mbar_wait(sb + BAR_WQF + 8 * pos, (s >> 3) & 1);
                const uint32_t da = make_desc(sb + wq_pos_off(pos) + h * 8192);
                const uint32_t db = make_desc(sb + OFF_Q + xs * 10240 + (s & 3) * 32);
                wg_fence();
#pragma unroll
                for (int m = 0; m < 4; m++) wgmma_n80<1>(o[m], da + m * 128, db, s > 0);
                wg_commit();
                wg_wait<1>();
                if (lane0) {
                    if (s >= 1 && s <= 20) mbar_arrive_both(sb, sbp, BAR_WQE + 8 * ((pos + 7) & 7));
                    if (s == 22) mbar_arrive(sb + BAR_KVE + 16);
                }
                pos = (pos + 1) & 7;
                if ((s & 3) == 3) xs = (xs == 2) ? 0 : xs + 1;
            }
        }
        wg_wait<0>();
#pragma unroll
        for (int m = 0; m < 4; m++) reg_fence(o[m]);
        bar_sync(NB_ALL, 256);
#pragma unroll
        for (int m = 0; m < 4; m++)
            store_tile_T_scaled(sb + OFF_Q + m * 20480 + h * 10240 + st_off, o[m], 0.09016844005556021f);
        fence_async_smem();
        if (lane0) mbar_arrive_both(sb, sbp, BAR_WOE);
        bar_sync(NB_WG + h, 128);
        if (tid == 0) TS(1);

        const uint32_t kHighBits = 0x4580, kLowBits = 0x3980;
        float l[20], s[40];
#pragma unroll
        for (int i = 0; i < 20; i++) l[i] = 0.0f;
#pragma unroll
        for (int i = 0; i < 40; i++) s[i] = 0.0f;
        const uint32_t nm_addr = sb + OFF_NM + h * 640 + (lane & 3) * 160;
        const uint32_t xch_base = sb + OFF_XCH + h * 1280 + (lane & 3) * 80;
        const uint32_t p_base = sb + OFF_P + h * 10240;
        int slot = 0, use = 0;
        bool has_ref = false;
        if (h == 1) bar_arrive(NB_TOK, 256);
        for (int it = 0; it < 16; it++) {
            bool exact = false;
            bool first = true;
            uint32_t pk[20];
            while (true) {
                if (first) {
                    CK(it, 0);
                    mbar_wait(sb + BAR_KVF + 8 * slot, use & 1);
                    CK(it, 1);
                    bar_sync(NB_TOK + h, 256);
                }
                const uint32_t da = make_desc(sb + OFF_KV + slot * 32768);
                const uint32_t db = make_desc(sb + OFF_Q + h * 10240);
                wg_fence();
#pragma unroll
                for (int kk = 0; kk < 16; kk++) {
                    wgmma_n80<0>(s, da + (kk >> 2) * 512 + (kk & 3) * 2, db + (kk >> 2) * 1280 + (kk & 3) * 2, 1);
                    if (kk == 15 - TOK_LEAD) wg_commit();
                }
                wg_commit();
                CK(it, 3);
                wg_wait<1>();
                if (first) bar_arrive(NB_TOK + (h ^ 1), 256);
                CK(it, 4);
                wg_wait<0>();
                reg_fence(s);
                CK(it, 5);
                if (exact) {
#pragma unroll
                    for (int j = 0; j < 10; j++) {
                        float m0 = fmaxf(s[4 * j + 0], s[4 * j + 2]);
                        float m1 = fmaxf(s[4 * j + 1], s[4 * j + 3]);
#pragma unroll
                        for (int d = 4; d < 32; d <<= 1) {
                            m0 = fmaxf(m0, __shfl_xor_sync(0xffffffffu, m0, d));
                            m1 = fmaxf(m1, __shfl_xor_sync(0xffffffffu, m1, d));
                        }
                        if (lane_id() < 4) sts64(xch_base + w * 320 + j * 8, m0, m1);
                    }
                    bar_sync(NB_WG + h, 128);
#pragma unroll
                    for (int g = 0; g < 5; g++) {
                        float4 d = lds128(xch_base + g * 16);
#pragma unroll
                        for (int ww = 1; ww < 4; ww++) {
                            const float4 e = lds128(xch_base + ww * 320 + g * 16);
                            d.x = fmaxf(d.x, e.x); d.y = fmaxf(d.y, e.y); d.z = fmaxf(d.z, e.z); d.w = fmaxf(d.w, e.w);
                        }
                        if (it > 0) {
                            d.x = fmaxf(d.x, 0.0f); d.y = fmaxf(d.y, 0.0f); d.z = fmaxf(d.z, 0.0f); d.w = fmaxf(d.w, 0.0f);
                        }
                        s[8 * g + 0] -= d.x; s[8 * g + 1] -= d.y; s[8 * g + 2] -= d.x; s[8 * g + 3] -= d.y;
                        s[8 * g + 4] -= d.z; s[8 * g + 5] -= d.w; s[8 * g + 6] -= d.z; s[8 * g + 7] -= d.w;
                        if (w == 0 && lane_id() < 4) {
                            float4 n0 = lds128(nm_addr + g * 32), n1 = lds128(nm_addr + g * 32 + 16);
                            n0.x -= d.x; n0.y -= d.y; n0.z -= d.x; n0.w -= d.y;
                            n1.x -= d.z; n1.y -= d.w; n1.z -= d.z; n1.w -= d.w;
                            sts128(nm_addr + g * 32, n0);
                            sts128(nm_addr + g * 32 + 16, n1);
                        }
                        if (it > 0) {
                            const float fx = ex2(-d.x), fy = ex2(-d.y), fz = ex2(-d.z), fw = ex2(-d.w);
                            l[4 * g + 0] *= fx; l[4 * g + 1] *= fy; l[4 * g + 2] *= fz; l[4 * g + 3] *= fw;
#pragma unroll
                            for (int m = 0; m < 4; m++) {
                                o[m][8 * g + 0] *= fx; o[m][8 * g + 1] *= fy; o[m][8 * g + 2] *= fx; o[m][8 * g + 3] *= fy;
                                o[m][8 * g + 4] *= fz; o[m][8 * g + 5] *= fw; o[m][8 * g + 6] *= fz; o[m][8 * g + 7] *= fw;
                            }
                        }
                    }
                }
                uint32_t mx = 0, mn = 0xffffffffu;
#pragma unroll
                for (int g = 0; g < 5; g++) {
#pragma unroll
                    for (int i = 0; i < 4; i++) pk[4 * g + i] = pack_bf16(ex2(s[8 * g + 2 * i]), ex2(s[8 * g + 2 * i + 1]));
                    stsm_x4_trans(p_base + st_off + g * 2048, pk[4 * g], pk[4 * g + 1], pk[4 * g + 2], pk[4 * g + 3]);
                    mx = __vimax3_u16x2(mx, pk[4 * g], pk[4 * g + 1]);
                    mx = __vimax3_u16x2(mx, pk[4 * g + 2], pk[4 * g + 3]);
                    mn = __vimin3_u16x2(mn, pk[4 * g], pk[4 * g + 1]);
                    mn = __vimin3_u16x2(mn, pk[4 * g + 2], pk[4 * g + 3]);
                }
                CK(it, 6);
                fence_async_smem();
                const bool low = (it == 0) && ((mn >> 16) < kLowBits || (mn & 0xffffu) < kLowBits);
                const bool over = __any_sync(0xffffffffu,
                    bar_red_or(NB_RED + h, 128, low || (mx >> 16) > kHighBits || (mx & 0xffffu) > kHighBits));
                if (!over || exact) break;
                exact = true;
                first = false;
                has_ref = true;
                load_nm(s, nm_addr);
            }
            if (lane0) {
                if (it < 15) mbar_arrive(sb + BAR_KVE + 8 * slot);
                else { mbar_arrive_both(sb, sbp, BAR_WOE + 8 * 3); mbar_arrive_both(sb, sbp, BAR_WOE + 8 * 4); }
            }
            if (++slot == 3) { slot = 0; use++; }
            {
                CK(it, 7);
                mbar_wait(sb + BAR_KVF + 8 * slot, use & 1);
                CK(it, 8);
                bar_sync(NB_TOK + h, 256);
                const uint32_t da = make_desc(sb + OFF_KV + slot * 32768);
                const uint32_t db = make_desc(p_base);
                wg_fence();
#pragma unroll
                for (int m = 0; m < 4; m++)
#pragma unroll
                    for (int kk = 0; kk < 4; kk++) {
                        wgmma_n80<1>(o[m], da + m * 512 + kk * 128, db + kk * 2, (it > 0) || (kk > 0));
                        if (4 * m + kk == 15 - TOK_LEAD) wg_commit();
                    }
                wg_commit();
            }
            CK(it, 10);
            wg_wait<1>();
            if (h == 0 || it < 15) bar_arrive(NB_TOK + (h ^ 1), 256);
            CK(it, 11);
            {
                uint32_t sh, msk;
                asm volatile("ld.shared.v2.u32 {%0, %1}, [%2];" : "=r"(sh), "=r"(msk) : "r"(sb + OFF_CONST) : "memory");
#pragma unroll
                for (int j = 0; j < 10; j++) {
                    l[2 * j + 0] += __uint_as_float(pk[2 * j] << sh) + __uint_as_float(pk[2 * j + 1] << sh);
                    l[2 * j + 1] += __uint_as_float(pk[2 * j] & msk) + __uint_as_float(pk[2 * j + 1] & msk);
                }
            }
            if (has_ref) load_nm(s, nm_addr);
            else {
#pragma unroll
                for (int i = 0; i < 40; i++) s[i] = 0.0f;
            }
            CK(it, 12);
            if (it < 15) {
                wg_wait<0>();
                CK(it, 13);
#pragma unroll
                for (int m = 0; m < 4; m++) reg_fence(o[m]);
                if (lane0) {
                    if (it < 14) mbar_arrive(sb + BAR_KVE + 8 * slot);
                    else { mbar_arrive_both(sb, sbp, BAR_WOE + 8 * 1); mbar_arrive_both(sb, sbp, BAR_WOE + 8 * 2); }
                }
                if (++slot == 3) { slot = 0; use++; }
            }
        }

        {
            const int ln = lane_id();
            const bool b4 = ln & 16, b3 = ln & 8;
            float a[10], c[5];
#pragma unroll
            for (int k = 0; k < 10; k++)
                a[k] = (b4 ? l[k + 10] : l[k]) + __shfl_xor_sync(0xffffffffu, b4 ? l[k] : l[k + 10], 16);
#pragma unroll
            for (int k = 0; k < 5; k++)
                c[k] = (b3 ? a[k + 5] : a[k]) + __shfl_xor_sync(0xffffffffu, b3 ? a[k] : a[k + 5], 8);
#pragma unroll
            for (int k = 0; k < 5; k++) c[k] += __shfl_xor_sync(0xffffffffu, c[k], 4);
            if (!(ln & 4)) {
#pragma unroll
                for (int k = 0; k < 5; k++)
                    asm volatile("st.shared.f32 [%0], %1;" ::"r"(xch_base + w * 320 + (ln >> 3) * 20 + k * 4), "f"(c[k]) : "memory");
            }
            CK(45, 0);
            bar_sync(NB_WG + h, 128);
            const int t = w * 32 + ln;
            if (t < 80) {
                const uint32_t xa = sb + OFF_XCH + h * 1280 + t * 4;
                float v0, v1, v2, v3;
                asm volatile("ld.shared.f32 %0, [%1];" : "=f"(v0) : "r"(xa) : "memory");
                asm volatile("ld.shared.f32 %0, [%1];" : "=f"(v1) : "r"(xa + 320) : "memory");
                asm volatile("ld.shared.f32 %0, [%1];" : "=f"(v2) : "r"(xa + 640) : "memory");
                asm volatile("ld.shared.f32 %0, [%1];" : "=f"(v3) : "r"(xa + 960) : "memory");
                asm volatile("st.shared.f32 [%0], %1;" ::"r"(xa), "f"(rcp_approx((v0 + v1) + (v2 + v3))) : "memory");
            }
            CK(45, 1);
            wg_wait<0>();
#pragma unroll
            for (int m = 0; m < 4; m++) reg_fence(o[m]);
            CK(45, 2);
            if (lane0) { mbar_arrive_both(sb, sbp, BAR_WOE + 8 * 5); mbar_arrive_both(sb, sbp, BAR_WOE + 8 * 6); }
            bar_sync(NB_WG + h, 128);
#pragma unroll
            for (int g = 0; g < 5; g++) {
                const float4 d = lds128(xch_base + g * 16);
                l[4 * g + 0] = d.x; l[4 * g + 1] = d.y; l[4 * g + 2] = d.z; l[4 * g + 3] = d.w;
            }
        }
        if (tid == 0) TS(2);
        CK(45, 3);

#pragma unroll
        for (int m = 0; m < 4; m++) {
#pragma unroll
            for (int g = 0; g < 5; g++) {
                stsm_x4_trans(sb + OFF_Q + m * 20480 + h * 10240 + st_off + g * 2048,
                              pack_bf16(o[m][8 * g + 0] * l[4 * g + 0], o[m][8 * g + 1] * l[4 * g + 1]),
                              pack_bf16(o[m][8 * g + 2] * l[4 * g + 0], o[m][8 * g + 3] * l[4 * g + 1]),
                              pack_bf16(o[m][8 * g + 4] * l[4 * g + 2], o[m][8 * g + 5] * l[4 * g + 3]),
                              pack_bf16(o[m][8 * g + 6] * l[4 * g + 2], o[m][8 * g + 7] * l[4 * g + 3]));
            }
        }
        CK(45, 4);
        fence_async_smem();
        CK(45, 5);
        bar_arrive(NB_O + (h ^ 1), 256);
        bar_sync(NB_WG + h, 128);
        if (tid == 0) TS(3);

        int pos = 0, ph = 0, prev = 0, st = 0;
        mbar_wait(sb + BAR_WOF, 0);
        auto stage = [&](float (&acc)[40], int q, bool half, bool ship) {
            CK(16 + st, 0);
            if (st == 4) bar_sync(NB_O + h, 256);
            const uint32_t da = make_desc(sb + wo_pos_off(pos) + h * 8192);
            const uint32_t db = make_desc(sb + OFF_Q + (q & 3) * 20480 + (half ? h : (q >> 2)) * 10240);
            wg_fence();
#pragma unroll
            for (int kk = 0; kk < 4; kk++) wgmma_n80<1>(acc, da + kk * 128, db + kk * 2, (q > 0) || (kk > 0));
            wg_commit();
            CK(16 + st, 1);
            if (ship) {
                fence_async_smem();
                bar_arrive(NB_OUT + h, 160);
            }
            const int cur = pos;
            if (++pos == 7) { pos = 0; ph ^= 1; }
            if (st < 27) mbar_wait(sb + BAR_WOF + 8 * pos, ph);
            CK(16 + st, 2);
            wg_wait<1>();
            CK(16 + st, 3);
            if (lane0 && st >= 1 && st <= 21) mbar_arrive_both(sb, sbp, BAR_WOE + 8 * prev);
            prev = cur;
            st++;
        };
#pragma unroll
        for (int t = 0; t < 5; t++) {
            const bool half = (t == (h ? 0 : 3));
            if (t < 4) stage(o[t & 3], 0, half, false);
            else wg_wait<0>();
            if (t > 0) {
                reg_fence(o[(t + 3) & 3]);
                if (t > 1) mbar_wait(sb + BAR_STG + 8 * h, t & 1);
                CK(15 + st, 4);
                store_tile_T(p_base + st_off, o[(t + 3) & 3]);
                CK(15 + st, 5);
                if (t == 4) {
                    fence_async_smem();
                    bar_arrive(NB_OUT + h, 160);
                }
            }
            if (t < 4) {
                const int nst = half ? 4 : 8;
#pragma unroll 1
                for (int q = 1; q < nst; q++) stage(o[t & 3], q, half, t > 0 && q == 1);
            }
        }
    }
}

typedef CUresult (*EncodeFn)(CUtensorMap*, CUtensorMapDataType, cuuint32_t, void*, const cuuint64_t*, const cuuint64_t*,
                             const cuuint32_t*, const cuuint32_t*, CUtensorMapInterleave, CUtensorMapSwizzle,
                             CUtensorMapL2promotion, CUtensorMapFloatOOBfill);

void encode_chunked(EncodeFn fn, CUtensorMap* m, const void* ptr, uint64_t rows, uint64_t cols, uint32_t box_rows,
                    uint32_t box_chunks) {
    cuuint64_t dims[3] = {64, rows, cols / 64};
    cuuint64_t strides[2] = {cols * 2, 128};
    cuuint32_t box[3] = {64, box_rows, box_chunks};
    cuuint32_t es[3] = {1, 1, 1};
    fn(m, CU_TENSOR_MAP_DATA_TYPE_BFLOAT16, 3, const_cast<void*>(ptr), dims, strides, box, es,
       CU_TENSOR_MAP_INTERLEAVE_NONE, CU_TENSOR_MAP_SWIZZLE_128B, PROMO,
       CU_TENSOR_MAP_FLOAT_OOB_FILL_NONE);
}

}

extern "C" void kernel_launch(void* const* d_in, const int* in_sizes, int n_in, void* d_out, int out_size) {
    (void)in_sizes; (void)n_in; (void)out_size;
    static EncodeFn fn = nullptr;
    if (!fn) {
        void* p = nullptr;
        cudaDriverEntryPointQueryResult qr;
        cudaGetDriverEntryPoint("cuTensorMapEncodeTiled", &p, cudaEnableDefault, &qr);
        fn = (EncodeFn)p;
        cudaFuncSetAttribute(fused_gqa_kernel, cudaFuncAttributeMaxDynamicSharedMemorySize, SMEM_BYTES);
    }
    Params prm;
    for (int br = 0; br < 2; br++) {
        encode_chunked(fn, &prm.x[br], d_in[5 * br + 0], kB * kSq, kD, 80, 1);
        encode_chunked(fn, &prm.k[br], d_in[5 * br + 1], (uint64_t)kB * kHkv * kSk, kDh, 64, 4);
        encode_chunked(fn, &prm.v[br], d_in[5 * br + 2], (uint64_t)kB * kHkv * kSk, kDh, 64, 4);
        encode_chunked(fn, &prm.wq[br], d_in[5 * br + 3], kD, 4096, 16, 4);
        encode_chunked(fn, &prm.wo[br], d_in[5 * br + 4], 4096, kD, 64, 1);
    }
    {
        cuuint64_t dims[2] = {2 * kD, kB * kSq};
        cuuint64_t strides[1] = {2 * kD * 2};
        cuuint32_t box[2] = {64, 80};
        cuuint32_t es[2] = {1, 1};
        fn(&prm.out, CU_TENSOR_MAP_DATA_TYPE_BFLOAT16, 2, d_out, dims, strides, box, es, CU_TENSOR_MAP_INTERLEAVE_NONE,
           CU_TENSOR_MAP_SWIZZLE_128B, CU_TENSOR_MAP_L2_PROMOTION_NONE, CU_TENSOR_MAP_FLOAT_OOB_FILL_NONE);
    }
    prm.outp = (__nv_bfloat16*)d_out;
    for (int br = 0; br < 2; br++) {
        prm.wop[br] = (const char*)d_in[5 * br + 4];
        prm.kp[br] = (const char*)d_in[5 * br + 1];
        prm.vp[br] = (const char*)d_in[5 * br + 2];
        for (int i = 0; i < 2; i++) {
            constexpr int M = KV_PF_MODE == 2 ? 2 : 1;
            cuuint64_t dims[2] = {64 * M, (cuuint64_t)kB * kHkv * kSk * 4 / M};
            cuuint64_t strides[1] = {128 * M};
            cuuint32_t box[2] = {8, 64};
            cuuint32_t es[2] = {1, 1};
            fn(i ? &prm.vl[br] : &prm.kl[br], CU_TENSOR_MAP_DATA_TYPE_BFLOAT16, 2, d_in[5 * br + 1 + i], dims, strides, box,
               es, CU_TENSOR_MAP_INTERLEAVE_NONE, CU_TENSOR_MAP_SWIZZLE_NONE, M == 2 ? CU_TENSOR_MAP_L2_PROMOTION_L2_256B : CU_TENSOR_MAP_L2_PROMOTION_L2_128B,
               CU_TENSOR_MAP_FLOAT_OOB_FILL_NONE);
        }
    }
    fused_gqa_kernel<<<128, kThreads, SMEM_BYTES>>>(prm);
}
```

```cpp
#include <cuda_runtime.h>
#include <cuda_bf16.h>
#include <cuda.h>
#include <stdint.h>

namespace {

constexpr int kB = 8, kSq = 80, kD = 448, kHkv = 8, kSk = 1024, kDh = 256;
constexpr int kThreads = 384;

constexpr uint32_t OFF_Q = 0;
constexpr uint32_t OFF_KV = 81920;
constexpr uint32_t OFF_P = OFF_KV + 3 * 32768;
constexpr uint32_t OFF_SPARE = OFF_P + 20480;
constexpr uint32_t OFF_ONES = OFF_SPARE + 24576;
constexpr uint32_t OFF_FAC = OFF_ONES - 640;
constexpr uint32_t OFF_XCH = OFF_SPARE + 28672 - 2560;
constexpr uint32_t OFF_MISC = OFF_SPARE + 28672;
constexpr uint32_t OFF_NM = OFF_MISC;
constexpr uint32_t OFF_BAR = OFF_MISC + 1280;
constexpr uint32_t OFF_JUNK = OFF_MISC + 2048;
constexpr uint32_t SMEM_BYTES = 232448;

constexpr uint32_t BAR_X = OFF_BAR;
constexpr uint32_t BAR_WQF = BAR_X + 7 * 8;
constexpr uint32_t BAR_WQE = BAR_WQF + 8 * 8;
constexpr uint32_t BAR_KVF = BAR_WQE + 8 * 8;
constexpr uint32_t BAR_KVE = BAR_KVF + 4 * 8;
constexpr uint32_t BAR_WOF = BAR_KVE + 4 * 8;
constexpr uint32_t BAR_WOE = BAR_WOF + 7 * 8;
constexpr uint32_t BAR_JUNK = BAR_WOE + 7 * 8;
constexpr uint32_t BAR_VB = BAR_JUNK + 8;

constexpr int NB_ALL = 1, NB_WG = 2, NB_RED = 4, NB_TOK = 6, NB_HELP = 8, NB_OUT = 9, NB_O = 11, NB_STG = 13;
__device__ __forceinline__ int nb_out(int h, int half) { return (half ? NB_RED : NB_OUT) + h; }
__device__ __forceinline__ int nb_stg(int h, int half) { return half ? (h ? NB_ALL : 15) : NB_STG + h; }

constexpr int KV_T0 = 1400;
constexpr int KV_PACE = 1313;
constexpr int KV_PHASE = 1600;
constexpr int KV_PF_LIMIT = 7;
constexpr int PH_SHRINK = 75;
constexpr int ZERO_AT = 25000;
constexpr int WO_STEP = 600;
constexpr int VA_DELAY = 320;
constexpr int VB_DELAY = 500;
__device__ __forceinline__ int kv_due(int j) { return KV_T0 + j * KV_PACE + (j == 31 ? VA_DELAY : 0); }
__device__ __forceinline__ bool chunk_is_v(int c) { return c == 31 || (c > 0 && !(c & 1)); }
__device__ __forceinline__ int chunk_tile(int c) { return c == 31 ? 15 : ((c & 1) ? (c + 1) >> 1 : max((c >> 1) - 1, 0)); }
constexpr int TOK_LEAD = 4;

struct Params {
    CUtensorMap x[2], k[2], v[2], wq[2], wo[2], kl[2], vl[2], out;
    __nv_bfloat16* outp;
};

__device__ unsigned int g_zero_cnt[16];

__device__ __forceinline__ unsigned long long gtime() {
    unsigned long long t;
    asm volatile("mov.u64 %0, %globaltimer;" : "=l"(t));
    return t;
}
__device__ __forceinline__ void pause_ns(int ns) {
    const uint32_t t0 = (uint32_t)gtime();
#pragma unroll 1
    for (int i = 0; i < 256; i++) {
        const int left = ns - (int)((uint32_t)gtime() - t0);
        if (left <= 0 || left > ns) break;
        __nanosleep(left > 200 ? (left >> 1) : 20);
    }
}

__device__ __forceinline__ void mbar_init(uint32_t bar, uint32_t cnt) {
    asm volatile("mbarrier.init.shared::cta.b64 [%0], %1;" ::"r"(bar), "r"(cnt) : "memory");
}
__device__ __forceinline__ void mbar_expect_tx(uint32_t bar, uint32_t bytes) {
    asm volatile("mbarrier.arrive.expect_tx.shared::cta.b64 _, [%0], %1;" ::"r"(bar), "r"(bytes) : "memory");
}
__device__ __forceinline__ void mbar_arrive(uint32_t bar) {
    asm volatile("mbarrier.arrive.shared::cta.b64 _, [%0];" ::"r"(bar) : "memory");
}
__device__ __forceinline__ void mbar_wait(uint32_t bar, uint32_t parity) {
    asm volatile(
        "{\n"
        ".reg .pred p;\n"
        ".reg .u32 n;\n"
        "mov.u32 n, 0;\n"
        "LAB_WAIT:\n"
        "mbarrier.try_wait.parity.shared::cta.b64 p, [%0], %1;\n"
        "@p bra LAB_DONE;\n"
        "add.u32 n, n, 1;\n"
        "setp.lt.u32 p, n, 4000000;\n"
        "@p bra LAB_WAIT;\n"
        "trap;\n"
        "LAB_DONE:\n"
        "}\n" ::"r"(bar), "r"(parity) : "memory");
}
__device__ __forceinline__ void tma_load_3d(uint32_t dst, const CUtensorMap* map, uint32_t bar, int c0, int c1, int c2) {
    asm volatile(
        "cp.async.bulk.tensor.3d.shared::cluster.global.mbarrier::complete_tx::bytes [%0], [%1, {%3, %4, %5}], [%2];"
        ::"r"(dst), "l"(map), "r"(bar), "r"(c0), "r"(c1), "r"(c2) : "memory");
}
__device__ __forceinline__ void tma_load_3d_hint(uint32_t dst, const CUtensorMap* map, uint32_t bar, int c0, int c1, int c2,
                                                 uint64_t pol) {
    asm volatile(
        "cp.async.bulk.tensor.3d.shared::cluster.global.mbarrier::complete_tx::bytes.L2::cache_hint"
        " [%0], [%1, {%3, %4, %5}], [%2], %6;"
        ::"r"(dst), "l"(map), "r"(bar), "r"(c0), "r"(c1), "r"(c2), "l"(pol) : "memory");
}
__device__ __forceinline__ void mbar_arrive2(uint32_t bar) {
    asm volatile("mbarrier.arrive.shared::cta.b64 _, [%0], 2;" ::"r"(bar) : "memory");
}
__device__ __forceinline__ bool mbar_test(uint32_t bar, uint32_t parity) {
    uint32_t r;
    asm volatile("{\n.reg .pred p;\nmbarrier.test_wait.parity.shared::cta.b64 p, [%1], %2;\nselp.u32 %0, 1, 0, p;\n}\n"
                 : "=r"(r) : "r"(bar), "r"(parity) : "memory");
    return r != 0;
}
__device__ __forceinline__ int lane_id() {
    int l;
    asm volatile("mov.u32 %0, %laneid;" : "=r"(l));
    return l;
}
__device__ __forceinline__ uint32_t kv_pos_off(int p) {
    return OFF_KV + (uint32_t)p * 16384 + (uint32_t)((p + 2) >> 3) * 20480;
}
__device__ __forceinline__ uint32_t wo_pos_off(int p) { return kv_pos_off(p + 1 - ((p + 2) >> 3) * 7); }
__device__ __forceinline__ void bar_arrive(int id, int n) { asm volatile("bar.arrive %0, %1;" ::"r"(id), "r"(n) : "memory"); }
__device__ __forceinline__ float rcp_approx(float x) {
    float y;
    asm("rcp.approx.ftz.f32 %0, %1;" : "=f"(y) : "f"(x));
    return y;
}
__device__ __forceinline__ void tma_touch_lines(uint32_t junk, const CUtensorMap* map, uint32_t bar, int line) {
    asm volatile(
        "cp.async.bulk.tensor.2d.shared::cluster.global.mbarrier::complete_tx::bytes [%0], [%1, {%3, %4}], [%2];"
        ::"r"(junk), "l"(map), "r"(bar), "r"(0), "r"(line) : "memory");
}
__device__ __forceinline__ int wo_row(int kvh, int st) {
    const int i = st >> 1;
    return kvh * 512 + ((((i < 2 ? i : i - 2) & 3) * 128) ^ ((st & 1) * 256));
}
__device__ __forceinline__ int wo_col(int st) { return st < 4 ? 6 : ((st - 4) >> 3) * 2 + (st & 1); }
__device__ __forceinline__ uint32_t wq_pos_off(int p) {
    return (p < 3 ? OFF_Q + 32768 : OFF_KV + 65536 - 3 * 16384) + (uint32_t)p * 16384;
}
__device__ __forceinline__ void prefetch_tmap(const CUtensorMap* map) {
    asm volatile("prefetch.tensormap [%0];" ::"l"(map) : "memory");
}
__device__ __forceinline__ void wg_fence() { asm volatile("wgmma.fence.sync.aligned;" ::: "memory"); }
__device__ __forceinline__ void wg_commit() { asm volatile("wgmma.commit_group.sync.aligned;" ::: "memory"); }
template <int N>
__device__ __forceinline__ void wg_wait() { asm volatile("wgmma.wait_group.sync.aligned %0;" ::"n"(N) : "memory"); }
__device__ __forceinline__ void fence_async_smem() { asm volatile("fence.proxy.async.shared::cta;" ::: "memory"); }
__device__ __forceinline__ void fence_async_all() { asm volatile("fence.proxy.async;" ::: "memory"); }
__device__ __forceinline__ void bar_sync(int id, int n) { asm volatile("bar.sync %0, %1;" ::"r"(id), "r"(n) : "memory"); }
__device__ __forceinline__ bool bar_red_or(int id, int n, bool pred) {
    uint32_t r;
    asm volatile(
        "{\n.reg .pred p, q;\nsetp.ne.u32 p, %3, 0;\nbar.red.or.pred q, %1, %2, p;\nselp.u32 %0, 1, 0, q;\n}\n"
        : "=r"(r) : "r"(id), "r"(n), "r"((uint32_t)pred) : "memory");
    return r != 0;
}
__device__ __forceinline__ void reg_fence(float (&d)[40]) {
#pragma unroll
    for (int i = 0; i < 40; i++) asm volatile("" : "+f"(d[i])::"memory");
}

__device__ __forceinline__ uint32_t make_desc(uint32_t addr) { return ((addr & 0x3FFFF) >> 4) | (1u << 16); }

template <int TRANS_A, uint32_t A_HI = 0x40000040>
__device__ __forceinline__ void wgmma_n80(float (&d)[40], uint32_t da, uint32_t db, uint32_t scale_d) {
    asm volatile(
        "{\n.reg .pred p;\n.reg .b64 da, db;\nsetp.ne.b32 p, %42, 0;\n"
        "mov.b64 da, {%40, %45};\nmov.b64 db, {%41, %44};\n"
        "wgmma.mma_async.sync.aligned.m64n80k16.f32.bf16.bf16 "
        "{%0, %1, %2, %3, %4, %5, %6, %7, %8, %9, %10, %11, %12, %13, %14, %15, %16, %17, %18, %19, "
        "%20, %21, %22, %23, %24, %25, %26, %27, %28, %29, %30, %31, %32, %33, %34, %35, %36, %37, %38, %39}, "
        "da, db, p, 1, 1, %43, 0;\n}\n"
        : "+f"(d[0]), "+f"(d[1]), "+f"(d[2]), "+f"(d[3]), "+f"(d[4]), "+f"(d[5]), "+f"(d[6]), "+f"(d[7]),
          "+f"(d[8]), "+f"(d[9]), "+f"(d[10]), "+f"(d[11]), "+f"(d[12]), "+f"(d[13]), "+f"(d[14]), "+f"(d[15]),
          "+f"(d[16]), "+f"(d[17]), "+f"(d[18]), "+f"(d[19]), "+f"(d[20]), "+f"(d[21]), "+f"(d[22]), "+f"(d[23]),
          "+f"(d[24]), "+f"(d[25]), "+f"(d[26]), "+f"(d[27]), "+f"(d[28]), "+f"(d[29]), "+f"(d[30]), "+f"(d[31]),
          "+f"(d[32]), "+f"(d[33]), "+f"(d[34]), "+f"(d[35]), "+f"(d[36]), "+f"(d[37]), "+f"(d[38]), "+f"(d[39])
        : "r"(da), "r"(db), "r"(scale_d), "n"(TRANS_A), "n"(0x40000040), "n"(A_HI));
}

template <uint32_t A_HI = 0x40000040>
__device__ __forceinline__ void wgmma_n80_init(float (&d)[40], uint32_t da, uint32_t db) {
    asm volatile(
        "{\n.reg .b64 da, db;\n"
        "mov.b64 da, {%40, %43};\nmov.b64 db, {%41, %42};\n"
        "wgmma.mma_async.sync.aligned.m64n80k16.f32.bf16.bf16 "
        "{%0, %1, %2, %3, %4, %5, %6, %7, %8, %9, %10, %11, %12, %13, %14, %15, %16, %17, %18, %19, "
        "%20, %21, %22, %23, %24, %25, %26, %27, %28, %29, %30, %31, %32, %33, %34, %35, %36, %37, %38, %39}, "
        "da, db, 0, 1, 1, 0, 0;\n}\n"
        : "=f"(d[0]), "=f"(d[1]), "=f"(d[2]), "=f"(d[3]), "=f"(d[4]), "=f"(d[5]), "=f"(d[6]), "=f"(d[7]),
          "=f"(d[8]), "=f"(d[9]), "=f"(d[10]), "=f"(d[11]), "=f"(d[12]), "=f"(d[13]), "=f"(d[14]), "=f"(d[15]),
          "=f"(d[16]), "=f"(d[17]), "=f"(d[18]), "=f"(d[19]), "=f"(d[20]), "=f"(d[21]), "=f"(d[22]), "=f"(d[23]),
          "=f"(d[24]), "=f"(d[25]), "=f"(d[26]), "=f"(d[27]), "=f"(d[28]), "=f"(d[29]), "=f"(d[30]), "=f"(d[31]),
          "=f"(d[32]), "=f"(d[33]), "=f"(d[34]), "=f"(d[35]), "=f"(d[36]), "=f"(d[37]), "=f"(d[38]), "=f"(d[39])
        : "r"(da), "r"(db), "n"(0x40000040), "n"(A_HI));
}

__device__ __forceinline__ uint32_t pack_bf16(float lo, float hi) {
    uint32_t r;
    asm("cvt.rn.bf16x2.f32 %0, %1, %2;" : "=r"(r) : "f"(hi), "f"(lo));
    return r;
}
__device__ __forceinline__ void stsm_x4_trans(uint32_t addr, uint32_t a, uint32_t b, uint32_t c, uint32_t d) {
    asm volatile("stmatrix.sync.aligned.m8n8.x4.trans.shared.b16 [%0], {%1, %2, %3, %4};"
                 ::"r"(addr), "r"(a), "r"(b), "r"(c), "r"(d) : "memory");
}
__device__ __forceinline__ void stsm_x2_trans(uint32_t addr, uint32_t a, uint32_t b) {
    asm volatile("stmatrix.sync.aligned.m8n8.x2.trans.shared.b16 [%0], {%1, %2};" ::"r"(addr), "r"(a), "r"(b) : "memory");
}
__device__ __forceinline__ void tma_reduce_out(const CUtensorMap* map, uint32_t src, int col, int row) {
    asm volatile("cp.reduce.async.bulk.tensor.2d.global.shared::cta.add.tile.bulk_group [%0, {%2, %3}], [%1];"
                 ::"l"(map), "r"(src), "r"(col), "r"(row) : "memory");
}
__device__ __forceinline__ float ex2(float x) {
    float y;
    asm("ex2.approx.ftz.f32 %0, %1;" : "=f"(y) : "f"(x));
    return y;
}
__device__ __forceinline__ float4 lds128(uint32_t addr) {
    float4 v;
    asm volatile("ld.shared.v4.f32 {%0, %1, %2, %3}, [%4];" : "=f"(v.x), "=f"(v.y), "=f"(v.z), "=f"(v.w) : "r"(addr) : "memory");
    return v;
}
__device__ __forceinline__ void sts128(uint32_t addr, float4 v) {
    asm volatile("st.shared.v4.f32 [%0], {%1, %2, %3, %4};" ::"r"(addr), "f"(v.x), "f"(v.y), "f"(v.z), "f"(v.w) : "memory");
}
__device__ __forceinline__ void sts64(uint32_t addr, float a, float b) {
    asm volatile("st.shared.v2.f32 [%0], {%1, %2};" ::"r"(addr), "f"(a), "f"(b) : "memory");
}

__device__ __forceinline__ void store_tile_T_scaled(uint32_t taddr, const float (&d)[40], float c) {
#pragma unroll
    for (int g = 0; g < 5; g++) {
        stsm_x4_trans(taddr + g * 2048, pack_bf16(d[8 * g + 0] * c, d[8 * g + 1] * c), pack_bf16(d[8 * g + 2] * c, d[8 * g + 3] * c),
                      pack_bf16(d[8 * g + 4] * c, d[8 * g + 5] * c), pack_bf16(d[8 * g + 6] * c, d[8 * g + 7] * c));
    }
}

__global__ void __launch_bounds__(kThreads, 1)
fused_gqa_kernel(const __grid_constant__ Params prm) {
    extern __shared__ __align__(1024) unsigned char smem_raw[];
    const uint32_t sb = (uint32_t)__cvta_generic_to_shared(smem_raw);
    const int tid = threadIdx.x;
    const int warp = __shfl_sync(0xffffffffu, tid >> 5, 0), lane = tid & 31;
    const int bidx = blockIdx.x;
    const int br = bidx >> 6;
    const int kvh = (bidx >> 3) & 7;
    const int b = bidx & 7;

    if (warp == 8 && lane == 0) {
        prefetch_tmap(&prm.wq[br]);
        prefetch_tmap(&prm.x[br]);
        mbar_init(sb + BAR_X, 1);
        mbar_init(sb + BAR_WQF + 8 * 7, 1);
        mbar_init(sb + BAR_WQF, 1);
        asm volatile("fence.mbarrier_init.release.cluster;" ::: "memory");
        mbar_expect_tx(sb + BAR_X, 10240);
        tma_load_3d(sb + OFF_Q, &prm.x[br], sb + BAR_X, 0, b * kSq, 0);
        for (int s = 0; s < 2; s++) {
            const int pos = (s + 7) & 7;
            mbar_expect_tx(sb + BAR_WQF + 8 * pos, 16384);
            tma_load_3d(sb + wq_pos_off(pos), &prm.wq[br], sb + BAR_WQF + 8 * pos, 0, 0, kvh * 8 + s * 4);
        }
    }
    if (warp == 9 && lane == 0) {
        if (sb & 1023) __trap();
        for (int i = 1; i < 7; i++) { mbar_init(sb + BAR_X + 8 * i, 1); mbar_init(sb + BAR_WQF + 8 * i, 1); }
        for (int i = 0; i < 8; i++) mbar_init(sb + BAR_WQE + 8 * i, 4);
        for (int i = 0; i < 4; i++) { mbar_init(sb + BAR_KVF + 8 * i, 1); mbar_init(sb + BAR_KVE + 8 * i, 8); }
        mbar_init(sb + BAR_JUNK, 1);
        mbar_init(sb + BAR_VB, 1);
        asm volatile("mbarrier.arrive.shared::cta.b64 _, [%0], 8;" ::"r"(sb + BAR_KVE) : "memory");
        asm volatile("mbarrier.arrive.shared::cta.b64 _, [%0], 8;" ::"r"(sb + BAR_KVE + 8) : "memory");
        asm volatile("fence.mbarrier_init.release.cluster;" ::: "memory");
    }
    if (warp == 10 && lane == 0) {
        for (int i = 0; i < 7; i++) { mbar_init(sb + BAR_WOF + 8 * i, 1); mbar_init(sb + BAR_WOE + 8 * i, 8); }
        asm volatile("fence.mbarrier_init.release.cluster;" ::: "memory");
    }
    if (tid < 256) {
        asm volatile("st.shared.f32 [%0], %1;" ::"r"(sb + OFF_NM + tid * 4), "f"(0.0f) : "memory");
        if (tid < 64) asm volatile("st.shared.f32 [%0], %1;" ::"r"(sb + OFF_NM + 1024 + tid * 4), "f"(0.0f) : "memory");
    }
    __syncthreads();

    if (warp >= 8) {
        asm volatile("setmaxnreg.dec.sync.aligned.u32 24;");
        if (warp == 8) {
            if (lane == 0) {
                const CUtensorMap* mw = &prm.wq[br];
                int pos = 1, ph = 0;
                for (int s = 2; s < 28; s++) {
                    if (s >= 8) mbar_wait(sb + BAR_WQE + 8 * pos, ((s >> 3) - 1) & 1);
                    mbar_expect_tx(sb + BAR_WQF + 8 * pos, 16384);
                    tma_load_3d(sb + wq_pos_off(pos), mw, sb + BAR_WQF + 8 * pos, 0, (s >> 1) * 32, kvh * 8 + (s & 1) * 4);
                    {
                        const int sp = (s == 7) ? 8 + b : ((s >= 8 && (s & 7) == b) ? s + 8 : 99);
                        if (sp < 28)
                            asm volatile("cp.async.bulk.prefetch.tensor.3d.L2.global.tile [%0, {%1, %2, %3}];"
                                         ::"l"(mw), "r"(0), "r"((sp >> 1) * 32), "r"(kvh * 8 + (sp & 1) * 4) : "memory");
                        if (s == 7 && kvh >= 3 && kvh < 7)
                            asm volatile("cp.async.bulk.prefetch.tensor.3d.L2.global.tile [%0, {%1, %2, %3}];"
                                         ::"l"(&prm.x[br]), "r"(0), "r"(b * kSq), "r"(kvh) : "memory");
                    }
                    if ((s & 3) == 3 && s < 24) {
                        const int c = (s + 1) >> 2;
                        mbar_expect_tx(sb + BAR_X + 8 * c, 10240);
                        tma_load_3d(sb + OFF_Q + (c % 3) * 10240, &prm.x[br], sb + BAR_X + 8 * c, 0, b * kSq, c);
                    }
                    pos = (pos + 1) & 7;
                }
                const CUtensorMap* mo = &prm.wo[br];
                prefetch_tmap(mo);
                pos = 0;
                for (int st = 0; st < 28; st++) {
                    if (st >= 7) mbar_wait(sb + BAR_WOF + 8 * pos, ph ^ 1);
                    mbar_expect_tx(sb + BAR_WOF + 8 * pos, 16384);
                    const int row = wo_row(kvh, st), col = wo_col(st);
                    mbar_wait(sb + BAR_WOE + 8 * pos, ph);
                    tma_load_3d(sb + wo_pos_off(pos), mo, sb + BAR_WOF + 8 * pos, 0, row, col);
                    if (++pos == 7) { pos = 0; ph ^= 1; }
                }
            }
        } else if (warp == 9) {
            if (lane == 0) {
                uint64_t pol;
                asm volatile("createpolicy.fractional.L2::evict_first.b64 %0, 1.0;" : "=l"(pol));
                const int row0 = (b * kHkv + kvh) * kSk;
                const int phase = (int)((((uint32_t)bidx >> 3) * 11u) & 15u) * KV_PHASE / 16;
                const uint32_t t0 = (uint32_t)gtime() + phase;
                const int shrink = (KV_PHASE / 2 - phase) * PH_SHRINK / (100 * 24);
                __nanosleep(800);
                prefetch_tmap(&prm.k[br]); prefetch_tmap(&prm.v[br]); prefetch_tmap(&prm.kl[br]); prefetch_tmap(&prm.vl[br]);
                int n = 0, pos = 0, pf = 0;
                uint32_t spins = 0;
                while (n < 64) {
                    const int c = n >> 1;
                    int left = kv_due(pf) + max(pf - 7, 0) * shrink - (int)((uint32_t)gtime() - t0);
                    if (left > 100000) left = 0;
                    const bool go = (c < pf || left <= 0);
                    const uint32_t ebar = sb + BAR_KVE + 8 * (n < 7 ? (n < 4 ? 0 : n >> 1) : ((n - 7) >> 1) & 3);
                    const uint32_t epar = n < 7 ? 0 : (((n - 7) >> 3) + 1) & 1;
                    if (go && pf >= KV_PF_LIMIT) mbar_wait(ebar, epar);
                    if (go && (pf >= KV_PF_LIMIT || mbar_test(ebar, epar))) {
                        uint32_t bar = sb + BAR_KVF + 8 * (c & 3);
                        if (n == 63) {
                            pause_ns(VB_DELAY);
                            bar = sb + BAR_VB;
                        }
                        if (!(n & 1) || n == 63) mbar_expect_tx(bar, n < 62 ? 32768 : 16384);
                        tma_load_3d_hint(sb + kv_pos_off(pos), chunk_is_v(c) ? &prm.v[br] : &prm.k[br], bar, 0,
                                         row0 + chunk_tile(c) * 64, (n & 1) * 2, pol);
                        if (++pos == 7) pos = 0;
                        n++;
                        if (c >= pf) pf = c + 1;
                    } else if (left <= 0) {
                        asm volatile("mbarrier.expect_tx.shared::cta.b64 [%0], %1;" ::"r"(sb + BAR_JUNK), "r"(2048) : "memory");
                        for (int i = 0; i < 2; i++)
                            tma_touch_lines(sb + OFF_JUNK, chunk_is_v(pf) ? &prm.vl[br] : &prm.kl[br], sb + BAR_JUNK,
                                            (row0 + chunk_tile(pf) * 64) * 2 + i * 64);
                        pf++;
                    } else {
                        __nanosleep((!go && left > 200) ? (left >> 1) : 30);
                        if (++spins > 100000000u) __trap();
                    }
                }
                mbar_wait(sb + BAR_VB, 0);
                for (int sp = 7 + b; sp < 28; sp += 8) {
                    asm volatile("cp.async.bulk.prefetch.tensor.3d.L2.global.tile [%0, {%1, %2, %3}];"
                                 ::"l"(&prm.wo[br]), "r"(0), "r"(wo_row(kvh, sp)), "r"(wo_col(sp)) : "memory");
                    pause_ns(WO_STEP);
                }
                mbar_arrive(sb + BAR_JUNK);
                mbar_wait(sb + BAR_JUNK, 0);
            }
        } else {
            const int t = tid - 320;
            pause_ns(ZERO_AT);
            __nv_bfloat16* o = prm.outp + (size_t)(b * kSq + kvh * 10) * (2 * kD) + br * kD;
            for (int i = t; i < 560; i += 64) {
                const int r = i / 56, c = i % 56;
                *reinterpret_cast<uint4*>(o + (size_t)r * (2 * kD) + c * 8) = make_uint4(0, 0, 0, 0);
            }
            fence_async_all();
            __threadfence();
            bar_sync(NB_HELP, 64);
            if (t == 0) {
                prefetch_tmap(&prm.out);
                unsigned int* cnt = &g_zero_cnt[br * 8 + b];
                unsigned int old;
                asm volatile("atom.add.release.gpu.global.u32 %0, [%1], 1;" : "=r"(old) : "l"(cnt) : "memory");
                const unsigned int target = (old & ~7u) + 8u;
                unsigned int cur, n = 0;
#pragma unroll 1
                do {
                    asm volatile("ld.acquire.gpu.global.u32 %0, [%1];" : "=r"(cur) : "l"(cnt) : "memory");
                    if ((int)(cur - target) >= 0) break;
                    __nanosleep(500);
                } while (++n < 4000000u);
                if ((int)(cur - target) < 0) __trap();
            }
            bar_sync(NB_HELP, 64);
            fence_async_all();
            const int h = warp - 10;
            for (int n = 0; n < 6; n++) {
                bar_sync(nb_out(h, n & 1), 160);
                fence_async_smem();
                if (lane == 0) {
                    const int tile = n < 2 ? 6 : (n & ~1) - 2 + h;
                    tma_reduce_out(&prm.out, sb + OFF_P + h * 10240 + (n & 1) * 5120, br * kD + tile * 64, b * kSq + (n & 1) * 40);
                    asm volatile("cp.async.bulk.commit_group;" ::: "memory");
                    asm volatile("cp.async.bulk.wait_group.read 0;" ::: "memory");
                }
                __syncwarp();
                if (n < 4) bar_arrive(nb_stg(h, n & 1), 160);
            }
        }
    } else {
        asm volatile("setmaxnreg.inc.sync.aligned.u32 240;");
        const int h = warp >> 2;
        const int w = warp & 3;
        auto tile_off = [&]() {
            const int ln = lane_id();
            return (uint32_t)(((ln >> 4) * 8 + (ln & 7)) * 128 + (((2 * w + ((ln >> 3) & 1)) ^ (ln & 7)) << 4));
        };

        float o[4][40];

        const bool lane0 = (lane == 0);

        {
            if (h == 1) bar_arrive(NB_TOK, 256);
            int pos = (7 + h) & 7, xs = 0;
            mbar_wait(sb + BAR_X, 0);
            mbar_wait(sb + BAR_WQF + 8 * pos, 0);
#pragma unroll 1
            for (int i = 0; i < 14; i++) {
                const uint32_t da = make_desc(sb + wq_pos_off(pos));
                const uint32_t db = make_desc(sb + OFF_Q + xs * 10240 + (i & 1) * 64);
                bar_sync(NB_TOK + h, 256);
                wg_fence();
#pragma unroll
                for (int kk = 0; kk < 2; kk++)
#pragma unroll
                    for (int m = 0; m < 4; m++) {
                        wgmma_n80<1>(o[m], da + kk * 128 + m * 256, db + kk * 2, (i > 0) || (kk > 0));
                        if (4 * kk + m == 7 - TOK_LEAD) wg_commit();
                    }
                wg_commit();
                wg_wait<1>();
                bar_arrive(NB_TOK + (h ^ 1), 256);
                const int cur = pos;
                pos = (pos + 2) & 7;
                if (i < 13) {
                    if (!__all_sync(0xffffffffu, mbar_test(sb + BAR_WQF + 8 * pos, ((i + 1) >> 2) & 1))) {
                        wg_wait<0>();
                        if (lane0 && i <= 9) mbar_arrive(sb + BAR_WQE + 8 * cur);
                        mbar_wait(sb + BAR_WQF + 8 * pos, ((i + 1) >> 2) & 1);
                    } else {
                        wg_wait<0>();
                        if (lane0 && i <= 9) mbar_arrive(sb + BAR_WQE + 8 * cur);
                    }
                    if (i & 1) mbar_wait(sb + BAR_X + 8 * ((i + 1) >> 1), 0);
                }
                if (lane0 && i == 10) mbar_arrive(sb + BAR_KVE + 16);
                if (i & 1) xs = (xs == 2) ? 0 : xs + 1;
            }
        }
        wg_wait<0>();
#pragma unroll
        for (int m = 0; m < 4; m++) reg_fence(o[m]);
        uint32_t st_off = tile_off();
        bar_sync(NB_ALL, 256);
#pragma unroll
        for (int m = 0; m < 4; m++)
            store_tile_T_scaled(sb + OFF_Q + m * 20480 + h * 10240 + st_off, o[m], 0.09016844005556021f);
        asm volatile("st.shared.u32 [%0], %1;" ::"r"(sb + OFF_ONES + tid * 4), "r"(0x3F803F80u) : "memory");
        fence_async_smem();
        if (lane0) mbar_arrive(sb + BAR_KVE + 24);

        float l[20], s[40];
#pragma unroll
        for (int i = 0; i < 20; i++) l[i] = 0.0f;
        const uint32_t nm_addr = sb + OFF_NM + h * 640 + (lane & 3) * 160;
        const uint32_t xch_base = sb + OFF_XCH + h * 1280 + (lane & 3) * 80;
        const uint32_t fac_addr = sb + OFF_FAC + h * 320 + (lane & 3) * 80;
        const uint32_t p_base = sb + OFF_P + h * 10240;
        int kc = 0, kp = 0;
        int has_ref = 0;
        bool ready = false;
        for (int it = 0; it < 16; it++) {
            uint32_t pk[20];
            bool move_ref;
            {
                if (!__all_sync(0xffffffffu, ready)) mbar_wait(sb + BAR_KVF + 8 * (kc & 3), (kc >> 2) & 1);
                const uint32_t da = make_desc(sb + kv_pos_off(kp)), da1 = make_desc(sb + wo_pos_off(kp)) - 1024;
                const uint32_t db = make_desc(sb + OFF_Q + h * 10240);
                bar_sync(NB_TOK + h, 256);
                wg_fence();
#pragma unroll
                for (int kk = 0; kk < 16; kk++) {
                    if (kk == 0) wgmma_n80_init(s, da, db);
                    else wgmma_n80<0>(s, (kk < 8 ? da : da1) + (kk >> 2) * 512 + (kk & 3) * 2, db + (kk >> 2) * 1280 + (kk & 3) * 2, 1);
                    if (kk == 15 - TOK_LEAD) wg_commit();
                }
                wg_commit();
                wg_wait<1>();
                bar_arrive(NB_TOK + (h ^ 1), 256);
                fence_async_smem();
                kc++;
                kp += kp < 5 ? 2 : -5;
                ready = mbar_test(sb + BAR_KVF + 8 * (kc & 3), (kc >> 2) & 1);
                wg_wait<0>();
                reg_fence(s);
                if (has_ref) {
#pragma unroll
                    for (int g = 0; g < 10; g++) {
                        const float4 v = lds128(nm_addr + g * 16);
                        s[4 * g + 0] += v.x; s[4 * g + 1] += v.y; s[4 * g + 2] += v.z; s[4 * g + 3] += v.w;
                    }
                }
                int hi[4];
#pragma unroll
                for (int c = 0; c < 4; c++) {
                    hi[c] = __vimax3_s32(__float_as_int(s[10 * c]), __float_as_int(s[10 * c + 1]), __float_as_int(s[10 * c + 2]));
#pragma unroll
                    for (int i = 3; i < 9; i += 2)
                        hi[c] = __vimax3_s32(hi[c], __float_as_int(s[10 * c + i]), __float_as_int(s[10 * c + i + 1]));
                }
                hi[0] = __vimax3_s32(hi[0], __float_as_int(s[9]), __float_as_int(s[19]));
                hi[1] = __vimax3_s32(hi[1], __float_as_int(s[29]), __float_as_int(s[39]));
                bool bad = __vimax3_s32(hi[0], hi[1], max(hi[2], hi[3])) > 0x42000000;
                if (it == 0) {
                    uint32_t lo = 0;
#pragma unroll
                    for (int i = 0; i < 40; i += 2) lo = __vimax3_u32(lo, __float_as_uint(s[i]), __float_as_uint(s[i + 1]));
                    bad = bad || lo > 0xC2000000u;
                }
                move_ref = __any_sync(0xffffffffu, bar_red_or(NB_RED + h, 128, bad));
                if (lane0) {
                    if (it < 15) mbar_arrive(sb + BAR_KVE + 8 * ((kc - 1) & 3));
                    else { mbar_arrive(sb + BAR_WOE + 8 * 1); mbar_arrive(sb + BAR_WOE + 8 * 2); }
                }
                if (move_ref) {
                    has_ref = 1;
#pragma unroll
                    for (int j = 0; j < 10; j++) {
                        float m0 = fmaxf(s[4 * j + 0], s[4 * j + 2]);
                        float m1 = fmaxf(s[4 * j + 1], s[4 * j + 3]);
#pragma unroll
                        for (int d = 4; d < 32; d <<= 1) {
                            m0 = fmaxf(m0, __shfl_xor_sync(0xffffffffu, m0, d));
                            m1 = fmaxf(m1, __shfl_xor_sync(0xffffffffu, m1, d));
                        }
                        if (lane_id() < 4) sts64(xch_base + w * 320 + j * 8, m0, m1);
                    }
                    bar_sync(NB_WG + h, 128);
#pragma unroll
                    for (int g = 0; g < 5; g++) {
                        float4 d = lds128(xch_base + g * 16);
#pragma unroll
                        for (int ww = 1; ww < 4; ww++) {
                            const float4 e = lds128(xch_base + ww * 320 + g * 16);
                            d.x = fmaxf(d.x, e.x); d.y = fmaxf(d.y, e.y); d.z = fmaxf(d.z, e.z); d.w = fmaxf(d.w, e.w);
                        }
                        if (it > 0) {
                            d.x = fmaxf(d.x, 0.0f); d.y = fmaxf(d.y, 0.0f); d.z = fmaxf(d.z, 0.0f); d.w = fmaxf(d.w, 0.0f);
                        }
                        s[8 * g + 0] -= d.x; s[8 * g + 1] -= d.y; s[8 * g + 2] -= d.x; s[8 * g + 3] -= d.y;
                        s[8 * g + 4] -= d.z; s[8 * g + 5] -= d.w; s[8 * g + 6] -= d.z; s[8 * g + 7] -= d.w;
                        if (w == 0 && lane_id() < 4) {
                            float4 n0 = lds128(nm_addr + g * 32), n1 = lds128(nm_addr + g * 32 + 16);
                            n0.x -= d.x; n0.y -= d.y; n0.z -= d.x; n0.w -= d.y;
                            n1.x -= d.z; n1.y -= d.w; n1.z -= d.z; n1.w -= d.w;
                            sts128(nm_addr + g * 32, n0);
                            sts128(nm_addr + g * 32 + 16, n1);
                        }
                        if (it > 0) {
                            const float4 f = make_float4(ex2(-d.x), ex2(-d.y), ex2(-d.z), ex2(-d.w));
                            l[4 * g + 0] *= f.x; l[4 * g + 1] *= f.y; l[4 * g + 2] *= f.z; l[4 * g + 3] *= f.w;
                            if (w == 0 && lane_id() < 4) sts128(fac_addr + g * 16, f);
                        }
                    }
                }
#pragma unroll
                for (int j = 0; j < 10; j++) {
                    const float p0 = ex2(s[4 * j]), p1 = ex2(s[4 * j + 1]), p2 = ex2(s[4 * j + 2]), p3 = ex2(s[4 * j + 3]);
                    pk[2 * j] = pack_bf16(p0, p1);
                    pk[2 * j + 1] = pack_bf16(p2, p3);
                    l[2 * j] += p0 + p2;
                    l[2 * j + 1] += p1 + p3;
                }
            }
            if (it == 15) {
                st_off = tile_off();
                const uint32_t qa = sb + OFF_Q + h * 10240 + st_off;
#pragma unroll
                for (int g = 0; g < 5; g++) {
                    stsm_x4_trans(qa + 2 * 20480 + g * 2048, pk[4 * g], pk[4 * g + 1], pk[4 * g + 2], pk[4 * g + 3]);
                    const uint32_t h0 = pack_bf16(l[4 * g], l[4 * g + 1]), h1 = pack_bf16(l[4 * g + 2], l[4 * g + 3]);
                    const uint32_t l0 = pack_bf16(l[4 * g] - __uint_as_float(h0 << 16), l[4 * g + 1] - __uint_as_float(h0 & 0xffff0000u));
                    const uint32_t l1 = pack_bf16(l[4 * g + 2] - __uint_as_float(h1 << 16), l[4 * g + 3] - __uint_as_float(h1 & 0xffff0000u));
                    stsm_x4_trans(qa + 3 * 20480 + g * 2048, h0, l0, h1, l1);
                }
                fence_async_smem();
            }
            if (it > 0) {
                if (!__all_sync(0xffffffffu, ready)) mbar_wait(sb + BAR_KVF + 8 * (kc & 3), (kc >> 2) & 1);
                const uint32_t da = make_desc(sb + kv_pos_off(kp)), da1 = make_desc(sb + wo_pos_off(kp)) - 1024;
                const uint32_t db = make_desc(p_base);
                bar_sync(NB_TOK + h, 256);
                wg_fence();
#pragma unroll
                for (int m = 0; m < 4; m++)
#pragma unroll
                    for (int kk = 0; kk < 4; kk++) {
                        wgmma_n80<1>(o[m], (m < 2 ? da : da1) + m * 512 + kk * 128, db + kk * 2, (it > 1) || (kk > 0));
                        if (4 * m + kk == 15 - TOK_LEAD) wg_commit();
                    }
                wg_commit();
                wg_wait<1>();
                bar_arrive(NB_TOK + (h ^ 1), 256);
                kc++;
                kp += kp < 5 ? 2 : -5;
                ready = mbar_test(sb + BAR_KVF + 8 * (kc & 3), (kc >> 2) & 1);
                wg_wait<0>();
#pragma unroll
                for (int m = 0; m < 4; m++) reg_fence(o[m]);
                if (lane0) {
                    if (it == 14) mbar_arrive(sb + BAR_WOE);
                    if (it < 15) mbar_arrive(sb + BAR_KVE + 8 * ((kc - 1) & 3));
                    else { mbar_arrive(sb + BAR_WOE + 8 * 3); mbar_arrive(sb + BAR_WOE + 8 * 4); }
                }
                if (move_ref) {
#pragma unroll
                    for (int g = 0; g < 5; g++) {
                        const float4 f = lds128(fac_addr + g * 16);
#pragma unroll
                        for (int m = 0; m < 4; m++) {
                            o[m][8 * g + 0] *= f.x; o[m][8 * g + 1] *= f.y; o[m][8 * g + 2] *= f.x; o[m][8 * g + 3] *= f.y;
                            o[m][8 * g + 4] *= f.z; o[m][8 * g + 5] *= f.w; o[m][8 * g + 6] *= f.z; o[m][8 * g + 7] *= f.w;
                        }
                    }
                }
            }
            if (it == 15) break;
            st_off = tile_off();
            bar_sync(NB_WG + h, 128);
#pragma unroll
            for (int g = 0; g < 5; g++)
                stsm_x4_trans(p_base + st_off + g * 2048, pk[4 * g], pk[4 * g + 1], pk[4 * g + 2], pk[4 * g + 3]);
        }

        {
            const uint32_t lt = sb + OFF_Q + 3 * 20480 + h * 10240;
            st_off = tile_off();
            wg_fence();
#pragma unroll
            for (int kk = 0; kk < 4; kk++) {
                if (kk == 0) wgmma_n80_init<0x40000000>(s, make_desc(sb + OFF_ONES), make_desc(lt));
                else wgmma_n80<0, 0x40000000>(s, make_desc(sb + OFF_ONES), make_desc(lt) + kk * 2, 1);
            }
            wg_commit();
            if (!__all_sync(0xffffffffu, ready)) mbar_wait(sb + BAR_KVF + 8 * (kc & 3), (kc >> 2) & 1);
            const uint32_t da = make_desc(sb + kv_pos_off(kp)), da1 = make_desc(sb + wo_pos_off(kp)) - 1024;
            const uint32_t db = make_desc(lt - 20480);
#pragma unroll
            for (int half = 0; half < 2; half++) {
                if (half == 1) mbar_wait(sb + BAR_VB, 0);
                bar_sync(NB_TOK + h, 256);
                wg_fence();
#pragma unroll
                for (int m = 2 * half; m < 2 * half + 2; m++) {
#pragma unroll
                    for (int kk = 0; kk < 4; kk++) wgmma_n80<1>(o[m], (m < 2 ? da : da1) + m * 512 + kk * 128, db + kk * 2, 1);
                    wg_commit();
                }
                wg_wait<1>();
                bar_arrive(NB_TOK + (h ^ 1), 256);
                if (half == 0) {
                    reg_fence(s);
#pragma unroll
                    for (int j = 0; j < 10; j++) { l[2 * j] = rcp_approx(s[4 * j]); l[2 * j + 1] = rcp_approx(s[4 * j + 1]); }
                } else {
                    mbar_wait(sb + BAR_WOF + 8 * h, 0);
                }
                wg_wait<0>();
                reg_fence(o[2 * half]);
                reg_fence(o[2 * half + 1]);
                if (lane0) mbar_arrive(sb + BAR_WOE + 8 * (5 + half));
                if (half == 1) bar_sync(NB_WG + h, 128);
#pragma unroll
                for (int m = 2 * half; m < 2 * half + 2; m++) {
#pragma unroll
                    for (int g = 0; g < 5; g++) {
                        stsm_x4_trans(sb + OFF_Q + m * 20480 + h * 10240 + st_off + g * 2048,
                                      pack_bf16(o[m][8 * g + 0] * l[4 * g + 0], o[m][8 * g + 1] * l[4 * g + 1]),
                                      pack_bf16(o[m][8 * g + 2] * l[4 * g + 0], o[m][8 * g + 3] * l[4 * g + 1]),
                                      pack_bf16(o[m][8 * g + 4] * l[4 * g + 2], o[m][8 * g + 5] * l[4 * g + 3]),
                                      pack_bf16(o[m][8 * g + 6] * l[4 * g + 2], o[m][8 * g + 7] * l[4 * g + 3]));
                    }
                }
            }
        }
        fence_async_smem();
        bar_arrive(NB_O + (h ^ 1), 256);

        uint32_t ot[20];
#pragma unroll
        for (int j = 0; j < 20; j++) ot[j] = 0;
        int pos = h, ph = 0;
#pragma unroll 1
        for (int i = 0; i < 14; i++) {
            if (i == 4) bar_sync(NB_O + h, 256);
            const int u = i < 2 ? i : i - 2;
            const uint32_t da = make_desc(sb + wo_pos_off(pos));
            const uint32_t db = make_desc(sb + OFF_Q + (u & 1) * 40960 + (((u >> 1) & 1) ^ h) * 10240);
            bar_sync(NB_TOK + h, 256);
            wg_fence();
#pragma unroll
            for (int kk = 0; kk < 8; kk++) {
                wgmma_n80<1>(o[0], da + kk * 128, db + (kk >> 2) * 1280 + (kk & 3) * 2, (u & 3) || (kk > 0));
                if (kk == 7 - TOK_LEAD) wg_commit();
            }
            wg_commit();
            wg_wait<1>();
            if (h == 0 || i < 13) bar_arrive(NB_TOK + (h ^ 1), 256);
            const int cur = pos;
            pos += 2;
            if (pos >= 7) { pos -= 7; ph ^= 1; }
            if (i < 13) mbar_wait(sb + BAR_WOF + 8 * pos, ph);
            else fence_async_smem();
            if (i >= 3 && (i & 1)) {
                bar_arrive(nb_out(h, !(i & 2)), 160);
                if (i >= 5 && i < 13) bar_sync(nb_stg(h, (i >> 1) & 1), 160);
            }
            wg_wait<0>();
            reg_fence(o[0]);
            if (lane0 && 2 * i + h <= 20) mbar_arrive2(sb + BAR_WOE + 8 * cur);
            if ((i & 3) == 1) {
#pragma unroll
                for (int j = 0; j < 20; j++) ot[j] = pack_bf16(o[0][2 * j], o[0][2 * j + 1]);
            }
            const uint32_t sa = p_base + st_off;
            if ((i & 3) == 1) { if (i < 13) stsm_x4_trans(sa, ot[0], ot[1], ot[2], ot[3]); }
            else if ((i & 3) == 2) { stsm_x4_trans(sa + 2048, ot[4], ot[5], ot[6], ot[7]); stsm_x2_trans(sa + 4096, ot[8], ot[9]); }
            else if ((i & 3) == 3) stsm_x4_trans(sa + 5120, ot[10], ot[11], ot[12], ot[13]);
            else if (i > 0) { stsm_x4_trans(sa + 7168, ot[14], ot[15], ot[16], ot[17]); stsm_x2_trans(sa + 9216, ot[18], ot[19]); }
        }
        {
            const uint32_t fin = sb + wo_pos_off(3 + h);
#pragma unroll
            for (int g = 0; g < 5; g++)
                stsm_x4_trans(p_base + st_off + (OFF_KV + 4 * 16384 - OFF_P + g * 2048) + h * (16384 - 10240), ot[4 * g], ot[4 * g + 1], ot[4 * g + 2], ot[4 * g + 3]);
            fence_async_smem();
            bar_sync(NB_WG + h, 128);
            if (lane_id() == 0 && w == 0) {
                tma_reduce_out(&prm.out, fin, br * kD + (4 + h) * 64, b * kSq);
                tma_reduce_out(&prm.out, fin + 5120, br * kD + (4 + h) * 64, b * kSq + 40);
                asm volatile("cp.async.bulk.commit_group;" ::: "memory");
                asm volatile("cp.async.bulk.wait_group.read 0;" ::: "memory");
            }
        }
    }
}

typedef CUresult (*EncodeFn)(CUtensorMap*, CUtensorMapDataType, cuuint32_t, void*, const cuuint64_t*, const cuuint64_t*,
                             const cuuint32_t*, const cuuint32_t*, CUtensorMapInterleave, CUtensorMapSwizzle,
                             CUtensorMapL2promotion, CUtensorMapFloatOOBfill);

void encode_chunked(EncodeFn fn, CUtensorMap* m, const void* ptr, uint64_t rows, uint64_t cols, uint32_t box_rows,
                    uint32_t box_chunks) {
    cuuint64_t dims[3] = {64, rows, cols / 64};
    cuuint64_t strides[2] = {cols * 2, 128};
    cuuint32_t box[3] = {64, box_rows, box_chunks};
    cuuint32_t es[3] = {1, 1, 1};
    fn(m, CU_TENSOR_MAP_DATA_TYPE_BFLOAT16, 3, const_cast<void*>(ptr), dims, strides, box, es,
       CU_TENSOR_MAP_INTERLEAVE_NONE, CU_TENSOR_MAP_SWIZZLE_128B, CU_TENSOR_MAP_L2_PROMOTION_L2_128B,
       CU_TENSOR_MAP_FLOAT_OOB_FILL_NONE);
}

}

extern "C" void kernel_launch(void* const* d_in, const int* in_sizes, int n_in, void* d_out, int out_size) {
    (void)in_sizes; (void)n_in; (void)out_size;
    static EncodeFn fn = nullptr;
    if (!fn) {
        void* p = nullptr;
        cudaDriverEntryPointQueryResult qr;
        cudaGetDriverEntryPoint("cuTensorMapEncodeTiled", &p, cudaEnableDefault, &qr);
        fn = (EncodeFn)p;
        cudaFuncSetAttribute(fused_gqa_kernel, cudaFuncAttributeMaxDynamicSharedMemorySize, SMEM_BYTES);
    }
    Params prm;
    for (int br = 0; br < 2; br++) {
        encode_chunked(fn, &prm.x[br], d_in[5 * br + 0], kB * kSq, kD, 80, 1);
        encode_chunked(fn, &prm.k[br], d_in[5 * br + 1], (uint64_t)kB * kHkv * kSk, kDh, 64, 2);
        encode_chunked(fn, &prm.v[br], d_in[5 * br + 2], (uint64_t)kB * kHkv * kSk, kDh, 64, 2);
        encode_chunked(fn, &prm.wq[br], d_in[5 * br + 3], kD, 4096, 32, 4);
        encode_chunked(fn, &prm.wo[br], d_in[5 * br + 4], 4096, kD, 128, 1);
    }
    {
        cuuint64_t dims[2] = {2 * kD, kB * kSq};
        cuuint64_t strides[1] = {2 * kD * 2};
        cuuint32_t box[2] = {64, 40};
        cuuint32_t es[2] = {1, 1};
        fn(&prm.out, CU_TENSOR_MAP_DATA_TYPE_BFLOAT16, 2, d_out, dims, strides, box, es, CU_TENSOR_MAP_INTERLEAVE_NONE,
           CU_TENSOR_MAP_SWIZZLE_128B, CU_TENSOR_MAP_L2_PROMOTION_NONE, CU_TENSOR_MAP_FLOAT_OOB_FILL_NONE);
    }
    prm.outp = (__nv_bfloat16*)d_out;
    for (int br = 0; br < 2; br++) {
        for (int i = 0; i < 2; i++) {
            cuuint64_t dims[2] = {128, (cuuint64_t)kB * kHkv * kSk * 2};
            cuuint64_t strides[1] = {256};
            cuuint32_t box[2] = {8, 64};
            cuuint32_t es[2] = {1, 1};
            fn(i ? &prm.vl[br] : &prm.kl[br], CU_TENSOR_MAP_DATA_TYPE_BFLOAT16, 2, d_in[5 * br + 1 + i], dims, strides, box,
               es, CU_TENSOR_MAP_INTERLEAVE_NONE, CU_TENSOR_MAP_SWIZZLE_NONE, CU_TENSOR_MAP_L2_PROMOTION_L2_256B,
               CU_TENSOR_MAP_FLOAT_OOB_FILL_NONE);
        }
    }
    fused_gqa_kernel<<<128, kThreads, SMEM_BYTES>>>(prm);
}
```
